```python
import torch

def _softmax(x, axis=-1):
    return torch.softmax(x, dim=axis)
def _gelu(x):
    return torch.nn.functional.gelu(x, approximate="tanh")
def _silu(x):
    return torch.nn.functional.silu(x)
def _sigmoid(x):
    return torch.sigmoid(x)
def _layernorm(x, axis=-1, eps=1e-5):
    m = x.mean(dim=axis, keepdim=True)
    v = x.var(dim=axis, keepdim=True, unbiased=False)
    return (x - m) / torch.sqrt(v + eps)
def _scatter_add(tgt, idx, src, axis=0):
    return tgt.clone().index_add_(axis, idx, src)
def _segment_sum(src, seg, n):
    out = torch.zeros((n,) + src.shape[1:], dtype=src.dtype)
    return out.index_add_(0, seg, src)
def _pad(x, pw):
    flat = tuple(v for pair in reversed(pw) for v in pair)
    return torch.nn.functional.pad(x, flat)

kernel_name = 'parallel_sum__ssm_conv_h3__dense_activation_gelu__prompt'

def setup_inputs():

    _w = (lambda a: (lambda t: t.to(torch.bfloat16) if t.is_floating_point() else t)(torch.as_tensor(a)))
    def _A_setup():
        B, S, D = 1, 2048, 640
        ks = 4
        return {
            "q": _w((lambda *s: torch.randn(*s, dtype=torch.bfloat16) * 0.05)(B, S, D)),
            "k": _w((lambda *s: torch.randn(*s, dtype=torch.bfloat16) * 0.2)(B, S, D)),
            "v": _w((lambda *s: torch.randn(*s, dtype=torch.bfloat16) * 0.2)(B, S, D)),
            "shift_k": _w((lambda *s: torch.randn(*s, dtype=torch.bfloat16) * 0.2)(D, ks) * 0.5),
            "ssm_k": _w((lambda *s: torch.randn(*s, dtype=torch.bfloat16) * 0.8)(D, S) * (1.0 / S ** 0.5)),
            "ssm_D": _w((lambda *s: torch.randn(*s, dtype=torch.bfloat16) * 0.2)(D)),
        }
    _A_in = _A_setup()

    def _B_setup():
        B, S, D, F = 1, 2048, 640, 1536
        return {
            "x": _w((lambda *s: torch.randn(*s, dtype=torch.bfloat16) * 0.05)(B, S, D)),
            "w1": _w((lambda *s: torch.randn(*s, dtype=torch.bfloat16) * 0.4)(D, F) * (D ** -0.5)),
            "b1": _w((lambda *s: torch.randn(*s, dtype=torch.bfloat16) * 12.8)(F) * 0.01),
            "w2": _w((lambda *s: torch.randn(*s, dtype=torch.bfloat16) * 0.2)(F, D) * (F ** -0.5)),
            "b2": _w((lambda *s: torch.randn(*s, dtype=torch.bfloat16) * 3.2)(D) * 0.01),
        }
    _B_in = _B_setup()

    return {
        "A_q": _A_in["q"],
        "A_k": _A_in["k"],
        "A_v": _A_in["v"],
        "A_shift_k": _A_in["shift_k"],
        "A_ssm_k": _A_in["ssm_k"],
        "A_ssm_D": _A_in["ssm_D"],
        "B_x": _B_in["x"],
        "B_w1": _B_in["w1"],
        "B_b1": _B_in["b1"],
        "B_w2": _B_in["w2"],
        "B_b2": _B_in["b2"],
    }

def reference(A_q, A_k, A_v, A_shift_k, A_ssm_k, A_ssm_D, B_x, B_w1, B_b1, B_w2, B_b2):
    def _A_ref(q, k, v, shift_k, ssm_k, ssm_D):
        B, S, D = q.shape
        ks = shift_k.shape[-1]
        k_pad = _pad(k, ((0, 0), (ks - 1, 0), (0, 0)))
        k_shift = torch.zeros_like(k)
        for t in range(ks):
            k_shift = k_shift + k_pad[:, t:t + S, :] * shift_k[:, ks - 1 - t][None, None, :]
        kv = k_shift * v
        L = 2 * S
        kv_pad = _pad(kv, ((0, 0), (0, S), (0, 0)))
        kf_pad = _pad(ssm_k, ((0, 0), (0, S)))
        kv_f = (lambda x, axes=(-2,-1): torch.fft.rfft2(x.float(), dim=axes))(kv_pad[:, None, :, :], axes=(1, 2))
        kf_f = (lambda x, axes=(-2,-1): torch.fft.rfft2(x.float(), dim=axes))(kf_pad[:, None, :], axes=(1, 2))
        kf_f = (lambda x, *d: x.permute(*d))(kf_f, 1, 2, 0)
        y_f = kv_f * kf_f[None, :, :, :]
        y = (lambda x, s, axes=(-2,-1): torch.fft.irfft2(x, s=s, dim=axes).to(torch.bfloat16))(y_f, (1, L), axes=(1, 2))[:, 0, :S, :]
        y = y + kv * ssm_D[None, None, :]
        return q * y

    def _B_ref(x, w1, b1, w2, b2):
        h = torch.einsum("bsd,df->bsf", x, w1) + b1
        h = _gelu(h)
        return torch.einsum("bsf,fd->bsd", h, w2) + b2

    x = A_q
    xn = _layernorm(x, axis=-1)
    return x + _A_ref(xn, A_k, A_v, A_shift_k, A_ssm_k, A_ssm_D) + _B_ref(xn, B_w1, B_b1, B_w2, B_b2)
```

```cpp
#include <cuda_runtime.h>
#include <cuda_bf16.h>
#include <cuda.h>
#include <stdint.h>

namespace {

constexpr int S_ = 2048, D_ = 640, F_ = 1536;
constexpr int NCTA = 132, NTHR = 384;
#define EARLY_KV 0
#define SLAB_PROMO CU_TENSOR_MAP_L2_PROMOTION_L2_128B
#define FIRST_GATE 2
constexpr int CONV_CL0 = 4, CONV_NCL = 18;

constexpr int C_KV = 0, C_Y = 10, C_LN = 15, C_CS = 31, C_INIT = 37, C_EPOCH = 38, C_NUM = 39;
struct Scratch {
  unsigned cnt[64 * 32];
  float2 stats[S_];
  float cs[4 * F_];
  __nv_bfloat16 ur[D_ * S_];
  __nv_bfloat16 yt[D_ * S_];
};
__device__ __align__(1024) Scratch g_scr;
extern __shared__ __align__(1024) uint8_t smem_raw[];
#define SMB ((uint32_t)__cvta_generic_to_shared(smem_raw))
#define STAMP(i) do {} while (0)
#define DUMP() do {} while (0)
#define TK(v)
#define AC(i, e)

constexpr int OFF_X = 0;
constexpr int OFF_W = 65536;
constexpr int OFF_C = OFF_W + 8 * 16384;
constexpr int ST_U = 0, ST_H0 = 4480, ST_H1 = 4480 + 4224 + 64, ST_BYTES = 13056;
constexpr int CA_MLP = 16384 + 4096 + ST_BYTES;
constexpr int CV_X = 0, CV_Y = 49152, CV_ST = 65536, CV_LN = CV_ST + 6 * ST_BYTES, LN_BYTES = 25600, CV_UX = CV_LN + 3 * LN_BYTES;
constexpr int OFF_STAT = OFF_C + CA_MLP;
constexpr int OFF_BAR = OFF_STAT + 1024;
constexpr int SMEM_BYTES = OFF_BAR + 320 + 256;
enum { B_WF = 0, B_WE = 4, B_BEXT = 8, B_U = 9, B_Y = 15, B_XT = 16, B_Z = 17, B_INIT = 18, B_NUM = 19, B_KV = B_WF, B_LN = B_WF + 2 };
static_assert(CV_UX + 2 * ST_H0 <= OFF_BAR, "smem");

__device__ __forceinline__ uint32_t smem_u32(const void* p) { return (uint32_t)__cvta_generic_to_shared(p); }
__device__ __forceinline__ void mbar_init(uint32_t b, int c) { asm volatile("mbarrier.init.shared::cta.b64 [%0], %1;" :: "r"(b), "r"(c)); }
__device__ __forceinline__ void mbar_expect(uint32_t b, uint32_t bytes) { asm volatile("mbarrier.arrive.expect_tx.shared::cta.b64 _, [%0], %1;" :: "r"(b), "r"(bytes) : "memory"); }
__device__ __forceinline__ void mbar_arrive(uint32_t b) { asm volatile("mbarrier.arrive.shared::cta.b64 _, [%0];" :: "r"(b) : "memory"); }
__device__ __forceinline__ void mbar_arrive_cl(uint32_t b) { asm volatile("mbarrier.arrive.shared::cluster.b64 _, [%0];" :: "r"(b) : "memory"); }
__device__ __forceinline__ void mbar_wait(uint32_t b, uint32_t ph) {
  asm volatile("{\n.reg .pred p;\n.reg .u32 n;\nmov.u32 n, 0;\nWL:\nmbarrier.try_wait.parity.shared::cta.b64 p, [%0], %1;\n@p bra WD;\n"
               "add.u32 n, n, 1;\nsetp.lt.u32 p, n, 1000000;\n@p bra WL;\nWD:\n}\n" :: "r"(b), "r"(ph) : "memory");
}
__device__ __forceinline__ uint32_t mapa(uint32_t a, uint32_t r) { uint32_t o; asm("mapa.shared::cluster.u32 %0, %1, %2;" : "=r"(o) : "r"(a), "r"(r)); return o; }
__device__ __forceinline__ void flag_wait(const unsigned* cnt, int c, unsigned target) {
  asm volatile("{\n.reg .pred p;\n.reg .u32 n, v;\nmov.u32 n, 0;\nFL:\nld.acquire.gpu.global.u32 v, [%0];\nsub.u32 v, v, %1;\nsetp.ge.s32 p, v, 0;\n@p bra FD;\n"
               "nanosleep.u32 20;\nadd.u32 n, n, 1;\nsetp.lt.u32 p, n, 2000000;\n@p bra FL;\nFD:\n}\n" :: "l"(cnt + c * 32), "r"(target) : "memory");
}
__device__ __forceinline__ bool elect() { uint32_t r; asm volatile("{.reg .pred p; elect.sync _|p, 0xffffffff; selp.u32 %0, 1, 0, p;}" : "=r"(r)); return r; }
__device__ __forceinline__ void flag_add(unsigned* cnt, int c) { asm volatile("red.release.gpu.global.add.u32 [%0], 1;" :: "l"(cnt + c * 32) : "memory"); }
__device__ __forceinline__ void fence_async() { asm volatile("fence.proxy.async.global;" ::: "memory"); }
__device__ __forceinline__ void fence_gpu() { asm volatile("fence.acq_rel.gpu;" ::: "memory"); }
__device__ __forceinline__ void flag_add_relaxed(unsigned* cnt, int c) { asm volatile("red.relaxed.gpu.global.add.u32 [%0], 1;" :: "l"(cnt + c * 32) : "memory"); }
__device__ __forceinline__ bool mbar_test(uint32_t b, uint32_t ph) {
  uint32_t ok; asm volatile("{.reg .pred p; mbarrier.test_wait.parity.shared::cta.b64 p, [%1], %2; selp.u32 %0, 1, 0, p;}" : "=r"(ok) : "r"(b), "r"(ph) : "memory"); return ok;
}
__device__ __forceinline__ void red4f(float* p, float a, float b, float c, float d) { asm volatile("red.relaxed.gpu.global.add.v4.f32 [%0], {%1,%2,%3,%4};" :: "l"(p), "f"(a), "f"(b), "f"(c), "f"(d) : "memory"); }
__device__ __forceinline__ void tma_prefetch3(const CUtensorMap* m, int y, int z) { asm volatile("cp.async.bulk.prefetch.tensor.3d.L2.global.tile [%0, {0, %1, %2}];" :: "l"(m), "r"(y), "r"(z) : "memory"); }
__device__ __forceinline__ void map_prefetch(const CUtensorMap* m) { asm volatile("prefetch.tensormap [%0];" :: "l"(m) : "memory"); }
__device__ __forceinline__ void fence_async_smem() { asm volatile("fence.proxy.async.shared::cta;" ::: "memory"); }
__device__ __forceinline__ void bar_sync(int id, int n) { asm volatile("bar.sync %0, %1;" :: "r"(id), "r"(n) : "memory"); }
__device__ __forceinline__ void bar_arrive(int id, int n) { asm volatile("bar.arrive %0, %1;" :: "r"(id), "r"(n) : "memory"); }
__device__ __forceinline__ void bulk_g2s(uint32_t dst, const void* src, uint32_t bytes, uint32_t bar) {
  asm volatile("cp.async.bulk.shared::cluster.global.mbarrier::complete_tx::bytes [%0], [%1], %2, [%3];" :: "r"(dst), "l"(src), "r"(bytes), "r"(bar) : "memory");
}
__device__ __forceinline__ void bulk_s2g(void* dst, uint32_t src, uint32_t bytes) {
  asm volatile("cp.async.bulk.global.shared::cta.bulk_group [%0], [%1], %2;" :: "l"(dst), "r"(src), "r"(bytes) : "memory");
}
__device__ __forceinline__ void tma_ld(uint32_t dst, const CUtensorMap* m, int x, int y, uint32_t bar) {
  asm volatile("cp.async.bulk.tensor.2d.shared::cluster.global.mbarrier::complete_tx::bytes [%0], [%1, {%3, %4}], [%2];"
               :: "r"(dst), "l"(m), "r"(bar), "r"(x), "r"(y) : "memory");
}
__device__ __forceinline__ void tma_ld3(uint32_t dst, const CUtensorMap* m, int y, int z, uint32_t bar) {
  asm volatile("cp.async.bulk.tensor.3d.shared::cluster.global.mbarrier::complete_tx::bytes [%0], [%1, {0, %3, %4}], [%2];"
               :: "r"(dst), "l"(m), "r"(bar), "r"(y), "r"(z) : "memory");
}
__device__ __forceinline__ void tma_ld3_mc(uint32_t dst, const CUtensorMap* m, int y, int z, uint32_t bar) {
  asm volatile("cp.async.bulk.tensor.3d.shared::cluster.global.mbarrier::complete_tx::bytes.multicast::cluster [%0], [%1, {0, %3, %4}], [%2], %5;"
               :: "r"(dst), "l"(m), "r"(bar), "r"(y), "r"(z), "h"((uint16_t)3) : "memory");
}
__device__ __forceinline__ void tma_ld3x(uint32_t dst, const CUtensorMap* m, int x, int y, uint32_t bar) {
  asm volatile("cp.async.bulk.tensor.3d.shared::cluster.global.mbarrier::complete_tx::bytes [%0], [%1, {%3, %4, 0}], [%2];"
               :: "r"(dst), "l"(m), "r"(bar), "r"(x), "r"(y) : "memory");
}
__device__ __forceinline__ void tma_red(const CUtensorMap* m, int x, int y, uint32_t src) {
  asm volatile("cp.reduce.async.bulk.tensor.2d.global.shared::cta.add.tile.bulk_group [%0, {%2, %3}], [%1];" :: "l"(m), "r"(src), "r"(x), "r"(y) : "memory");
}
__device__ __forceinline__ void bulk_commit() { asm volatile("cp.async.bulk.commit_group;" ::: "memory"); }
template <int N> __device__ __forceinline__ void bulk_wait_read() { asm volatile("cp.async.bulk.wait_group.read %0;" :: "n"(N) : "memory"); }
template <int N> __device__ __forceinline__ void bulk_wait() { asm volatile("cp.async.bulk.wait_group %0;" :: "n"(N) : "memory"); }
__device__ __forceinline__ void wg_fence() { asm volatile("wgmma.fence.sync.aligned;" ::: "memory"); }
__device__ __forceinline__ void wg_commit() { asm volatile("wgmma.commit_group.sync.aligned;" ::: "memory"); }
template <int N> __device__ __forceinline__ void wg_wait() { asm volatile("wgmma.wait_group.sync.aligned %0;" :: "n"(N) : "memory"); }
__device__ __forceinline__ uint32_t lds32(uint32_t a) { uint32_t v; asm volatile("ld.shared.u32 %0, [%1];" : "=r"(v) : "r"(a)); return v; }
__device__ __forceinline__ void sts32(uint32_t a, uint32_t v) { asm volatile("st.shared.u32 [%0], %1;" :: "r"(a), "r"(v) : "memory"); }
__device__ __forceinline__ void sts32p(uint32_t a, uint32_t v, bool p) { asm volatile("{.reg .pred q; setp.ne.b32 q, %2, 0; @q st.shared.u32 [%0], %1;}" :: "r"(a), "r"(v), "r"((int)p) : "memory"); }
__device__ __forceinline__ void sts128(uint32_t a, uint32_t x, uint32_t y, uint32_t z, uint32_t w) { asm volatile("st.shared.v4.u32 [%0], {%1,%2,%3,%4};" :: "r"(a), "r"(x), "r"(y), "r"(z), "r"(w) : "memory"); }
__device__ __forceinline__ uint4 lds128(uint32_t a) { uint4 v; asm volatile("ld.shared.v4.u32 {%0,%1,%2,%3}, [%4];" : "=r"(v.x), "=r"(v.y), "=r"(v.z), "=r"(v.w) : "r"(a) : "memory"); return v; }
__device__ __forceinline__ uint2 lds64(uint32_t a) { uint2 v; asm volatile("ld.shared.v2.u32 {%0,%1}, [%2];" : "=r"(v.x), "=r"(v.y) : "r"(a) : "memory"); return v; }
__device__ __forceinline__ void st128(void* p, uint32_t x, uint32_t y, uint32_t z, uint32_t w) { asm volatile("st.v4.u32 [%0], {%1,%2,%3,%4};" :: "l"(p), "r"(x), "r"(y), "r"(z), "r"(w) : "memory"); }
__device__ __forceinline__ uint4 lds128_ro(uint32_t a) { uint4 v; asm("ld.shared.v4.u32 {%0,%1,%2,%3}, [%4];" : "=r"(v.x), "=r"(v.y), "=r"(v.z), "=r"(v.w) : "r"(a)); return v; }
__device__ __forceinline__ float2 lds64f(uint32_t a) { float2 v; asm volatile("ld.shared.v2.f32 {%0,%1}, [%2];" : "=f"(v.x), "=f"(v.y) : "r"(a) : "memory"); return v; }
__device__ __forceinline__ float4 lds128f(uint32_t a) { float4 v; asm volatile("ld.shared.v4.f32 {%0,%1,%2,%3}, [%4];" : "=f"(v.x), "=f"(v.y), "=f"(v.z), "=f"(v.w) : "r"(a)); return v; }
__device__ __forceinline__ void stsm4(uint32_t a, uint32_t x, uint32_t y, uint32_t z, uint32_t w) { asm volatile("stmatrix.sync.aligned.m8n8.x4.shared.b16 [%0], {%1,%2,%3,%4};" :: "r"(a), "r"(x), "r"(y), "r"(z), "r"(w) : "memory"); }
__device__ __forceinline__ void stsm4t(uint32_t a, uint32_t x, uint32_t y, uint32_t z, uint32_t w) { asm volatile("stmatrix.sync.aligned.m8n8.x4.trans.shared.b16 [%0], {%1,%2,%3,%4};" :: "r"(a), "r"(x), "r"(y), "r"(z), "r"(w) : "memory"); }
__device__ __forceinline__ void ldsm4(uint32_t a, uint32_t* r) { asm volatile("ldmatrix.sync.aligned.m8n8.x4.shared.b16 {%0,%1,%2,%3}, [%4];" : "=r"(r[0]), "=r"(r[1]), "=r"(r[2]), "=r"(r[3]) : "r"(a) : "memory"); }
__device__ __forceinline__ void ldsm4t(uint32_t a, uint32_t* r) { asm volatile("ldmatrix.sync.aligned.m8n8.x4.trans.shared.b16 {%0,%1,%2,%3}, [%4];" : "=r"(r[0]), "=r"(r[1]), "=r"(r[2]), "=r"(r[3]) : "r"(a) : "memory"); }
__device__ __forceinline__ uint32_t pack2(float lo, float hi) { uint32_t r; asm("cvt.rn.bf16x2.f32 %0, %1, %2;" : "=r"(r) : "f"(hi), "f"(lo)); return r; }
__device__ __forceinline__ float bf_lo(uint32_t v) { return __uint_as_float(v << 16); }
__device__ __forceinline__ float bf_hi(uint32_t v) { return __uint_as_float(v & 0xffff0000u); }
__device__ __forceinline__ float bf_round(float v) { return bf_lo(pack2(v, 0.f)); }
__device__ __forceinline__ uint32_t hadd2(uint32_t a, uint32_t b) { uint32_t r; asm("add.rn.bf16x2 %0, %1, %2;" : "=r"(r) : "r"(a), "r"(b)); return r; }
__device__ __forceinline__ uint32_t hsub2(uint32_t a, uint32_t b) { uint32_t r; asm("sub.rn.bf16x2 %0, %1, %2;" : "=r"(r) : "r"(a), "r"(b)); return r; }
__device__ __forceinline__ uint32_t hmul2(uint32_t a, uint32_t b) { uint32_t r; asm("mul.rn.bf16x2 %0, %1, %2;" : "=r"(r) : "r"(a), "r"(b)); return r; }
__device__ __forceinline__ uint32_t hfma2(uint32_t a, uint32_t b, uint32_t c) { uint32_t r; asm("fma.rn.bf16x2 %0, %1, %2, %3;" : "=r"(r) : "r"(a), "r"(b), "r"(c)); return r; }
__device__ __forceinline__ float tanh_fast(float x) { float r; asm("tanh.approx.f32 %0, %1;" : "=f"(r) : "f"(x)); return r; }
__device__ __forceinline__ float rcp_fast(float x) { float r; asm("rcp.approx.ftz.f32 %0, %1;" : "=f"(r) : "f"(x)); return r; }
__device__ __forceinline__ float rsqrt_fast(float x) { float r; asm("rsqrt.approx.ftz.f32 %0, %1;" : "=f"(r) : "f"(x)); return r; }
__device__ __forceinline__ uint4 ldg128(const void* p) { uint4 v; asm volatile("ld.global.nc.L1::no_allocate.v4.u32 {%0,%1,%2,%3}, [%4];" : "=r"(v.x), "=r"(v.y), "=r"(v.z), "=r"(v.w) : "l"(p)); return v; }
__device__ __forceinline__ uint2 ldg64(const void* p) { uint2 v; asm volatile("ld.global.nc.v2.u32 {%0,%1}, [%2];" : "=r"(v.x), "=r"(v.y) : "l"(p)); return v; }
__device__ __forceinline__ uint32_t ldg32(const void* p) { uint32_t v; asm volatile("ld.global.nc.u32 %0, [%1];" : "=r"(v) : "l"(p)); return v; }
__device__ __forceinline__ float4 ldcg128f(const void* p) { float4 v; asm volatile("ld.global.cg.v4.f32 {%0,%1,%2,%3}, [%4];" : "=f"(v.x), "=f"(v.y), "=f"(v.z), "=f"(v.w) : "l"(p) : "memory"); return v; }
__device__ __forceinline__ float2 ldcg64f(const void* p) { float2 v; asm volatile("ld.global.cg.v2.f32 {%0,%1}, [%2];" : "=f"(v.x), "=f"(v.y) : "l"(p) : "memory"); return v; }
__device__ __forceinline__ void stg128(void* p, uint32_t x, uint32_t y, uint32_t z, uint32_t w) { asm volatile("st.global.v4.u32 [%0], {%1,%2,%3,%4};" :: "l"(p), "r"(x), "r"(y), "r"(z), "r"(w) : "memory"); }
__device__ __forceinline__ void cluster_arrive() { asm volatile("barrier.cluster.arrive.relaxed.aligned;" ::: "memory"); }
__device__ __forceinline__ void cluster_wait() { asm volatile("barrier.cluster.wait.acquire.aligned;" ::: "memory"); }

__device__ __forceinline__ void wg_ss256(float (&d)[128], uint32_t alo, uint32_t blo, uint32_t sc) {
  asm volatile("{\n.reg .pred p;\n.reg .b64 da, db;\nmov.b64 da, {%128, 0x40000040};\nmov.b64 db, {%129, 0x40000040};\nsetp.ne.b32 p, %130, 0;\n"
    "wgmma.mma_async.sync.aligned.m64n256k16.f32.bf16.bf16 {%0, %1, %2, %3, %4, %5, %6, %7, %8, %9, %10, %11, %12, %13, %14, %15, %16, %17, %18, %19, %20, %21, %22, %23, %24, %25, %26, %27, %28, %29, %30, %31, %32, %33, %34, %35, %36, %37, %38, %39, %40, %41, %42, %43, %44, %45, %46, %47, %48, %49, %50, %51, %52, %53, %54, %55, %56, %57, %58, %59, %60, %61, %62, %63, %64, %65, %66, %67, %68, %69, %70, %71, %72, %73, %74, %75, %76, %77, %78, %79, %80, %81, %82, %83, %84, %85, %86, %87, %88, %89, %90, %91, %92, %93, %94, %95, %96, %97, %98, %99, %100, %101, %102, %103, %104, %105, %106, %107, %108, %109, %110, %111, %112, %113, %114, %115, %116, %117, %118, %119, %120, %121, %122, %123, %124, %125, %126, %127}, da, db, p, 1, 1, 0, 1;\n}\n"
    : "+f"(d[0]), "+f"(d[1]), "+f"(d[2]), "+f"(d[3]), "+f"(d[4]), "+f"(d[5]), "+f"(d[6]), "+f"(d[7]), "+f"(d[8]), "+f"(d[9]), "+f"(d[10]), "+f"(d[11]), "+f"(d[12]), "+f"(d[13]), "+f"(d[14]), "+f"(d[15]), "+f"(d[16]), "+f"(d[17]), "+f"(d[18]), "+f"(d[19]), "+f"(d[20]), "+f"(d[21]), "+f"(d[22]), "+f"(d[23]), "+f"(d[24]), "+f"(d[25]), "+f"(d[26]), "+f"(d[27]), "+f"(d[28]), "+f"(d[29]), "+f"(d[30]), "+f"(d[31]), "+f"(d[32]), "+f"(d[33]), "+f"(d[34]), "+f"(d[35]), "+f"(d[36]), "+f"(d[37]), "+f"(d[38]), "+f"(d[39]), "+f"(d[40]), "+f"(d[41]), "+f"(d[42]), "+f"(d[43]), "+f"(d[44]), "+f"(d[45]), "+f"(d[46]), "+f"(d[47]), "+f"(d[48]), "+f"(d[49]), "+f"(d[50]), "+f"(d[51]), "+f"(d[52]), "+f"(d[53]), "+f"(d[54]), "+f"(d[55]), "+f"(d[56]), "+f"(d[57]), "+f"(d[58]), "+f"(d[59]), "+f"(d[60]), "+f"(d[61]), "+f"(d[62]), "+f"(d[63]), "+f"(d[64]), "+f"(d[65]), "+f"(d[66]), "+f"(d[67]), "+f"(d[68]), "+f"(d[69]), "+f"(d[70]), "+f"(d[71]), "+f"(d[72]), "+f"(d[73]), "+f"(d[74]), "+f"(d[75]), "+f"(d[76]), "+f"(d[77]), "+f"(d[78]), "+f"(d[79]), "+f"(d[80]), "+f"(d[81]), "+f"(d[82]), "+f"(d[83]), "+f"(d[84]), "+f"(d[85]), "+f"(d[86]), "+f"(d[87]), "+f"(d[88]), "+f"(d[89]), "+f"(d[90]), "+f"(d[91]), "+f"(d[92]), "+f"(d[93]), "+f"(d[94]), "+f"(d[95]), "+f"(d[96]), "+f"(d[97]), "+f"(d[98]), "+f"(d[99]), "+f"(d[100]), "+f"(d[101]), "+f"(d[102]), "+f"(d[103]), "+f"(d[104]), "+f"(d[105]), "+f"(d[106]), "+f"(d[107]), "+f"(d[108]), "+f"(d[109]), "+f"(d[110]), "+f"(d[111]), "+f"(d[112]), "+f"(d[113]), "+f"(d[114]), "+f"(d[115]), "+f"(d[116]), "+f"(d[117]), "+f"(d[118]), "+f"(d[119]), "+f"(d[120]), "+f"(d[121]), "+f"(d[122]), "+f"(d[123]), "+f"(d[124]), "+f"(d[125]), "+f"(d[126]), "+f"(d[127]) : "r"(alo), "r"(blo), "r"(sc));
}
__device__ __forceinline__ void wg_rs256(float (&d)[128], uint32_t a0, uint32_t a1, uint32_t a2, uint32_t a3, uint32_t blo) {
  asm volatile("{\n.reg .b64 db;\nmov.b64 db, {%132, 0x40000040};\n"
    "wgmma.mma_async.sync.aligned.m64n256k16.f32.bf16.bf16 {%0, %1, %2, %3, %4, %5, %6, %7, %8, %9, %10, %11, %12, %13, %14, %15, %16, %17, %18, %19, %20, %21, %22, %23, %24, %25, %26, %27, %28, %29, %30, %31, %32, %33, %34, %35, %36, %37, %38, %39, %40, %41, %42, %43, %44, %45, %46, %47, %48, %49, %50, %51, %52, %53, %54, %55, %56, %57, %58, %59, %60, %61, %62, %63, %64, %65, %66, %67, %68, %69, %70, %71, %72, %73, %74, %75, %76, %77, %78, %79, %80, %81, %82, %83, %84, %85, %86, %87, %88, %89, %90, %91, %92, %93, %94, %95, %96, %97, %98, %99, %100, %101, %102, %103, %104, %105, %106, %107, %108, %109, %110, %111, %112, %113, %114, %115, %116, %117, %118, %119, %120, %121, %122, %123, %124, %125, %126, %127}, {%128,%129,%130,%131}, db, 1, 1, 1, 1;\n}\n"
    : "+f"(d[0]), "+f"(d[1]), "+f"(d[2]), "+f"(d[3]), "+f"(d[4]), "+f"(d[5]), "+f"(d[6]), "+f"(d[7]), "+f"(d[8]), "+f"(d[9]), "+f"(d[10]), "+f"(d[11]), "+f"(d[12]), "+f"(d[13]), "+f"(d[14]), "+f"(d[15]), "+f"(d[16]), "+f"(d[17]), "+f"(d[18]), "+f"(d[19]), "+f"(d[20]), "+f"(d[21]), "+f"(d[22]), "+f"(d[23]), "+f"(d[24]), "+f"(d[25]), "+f"(d[26]), "+f"(d[27]), "+f"(d[28]), "+f"(d[29]), "+f"(d[30]), "+f"(d[31]), "+f"(d[32]), "+f"(d[33]), "+f"(d[34]), "+f"(d[35]), "+f"(d[36]), "+f"(d[37]), "+f"(d[38]), "+f"(d[39]), "+f"(d[40]), "+f"(d[41]), "+f"(d[42]), "+f"(d[43]), "+f"(d[44]), "+f"(d[45]), "+f"(d[46]), "+f"(d[47]), "+f"(d[48]), "+f"(d[49]), "+f"(d[50]), "+f"(d[51]), "+f"(d[52]), "+f"(d[53]), "+f"(d[54]), "+f"(d[55]), "+f"(d[56]), "+f"(d[57]), "+f"(d[58]), "+f"(d[59]), "+f"(d[60]), "+f"(d[61]), "+f"(d[62]), "+f"(d[63]), "+f"(d[64]), "+f"(d[65]), "+f"(d[66]), "+f"(d[67]), "+f"(d[68]), "+f"(d[69]), "+f"(d[70]), "+f"(d[71]), "+f"(d[72]), "+f"(d[73]), "+f"(d[74]), "+f"(d[75]), "+f"(d[76]), "+f"(d[77]), "+f"(d[78]), "+f"(d[79]), "+f"(d[80]), "+f"(d[81]), "+f"(d[82]), "+f"(d[83]), "+f"(d[84]), "+f"(d[85]), "+f"(d[86]), "+f"(d[87]), "+f"(d[88]), "+f"(d[89]), "+f"(d[90]), "+f"(d[91]), "+f"(d[92]), "+f"(d[93]), "+f"(d[94]), "+f"(d[95]), "+f"(d[96]), "+f"(d[97]), "+f"(d[98]), "+f"(d[99]), "+f"(d[100]), "+f"(d[101]), "+f"(d[102]), "+f"(d[103]), "+f"(d[104]), "+f"(d[105]), "+f"(d[106]), "+f"(d[107]), "+f"(d[108]), "+f"(d[109]), "+f"(d[110]), "+f"(d[111]), "+f"(d[112]), "+f"(d[113]), "+f"(d[114]), "+f"(d[115]), "+f"(d[116]), "+f"(d[117]), "+f"(d[118]), "+f"(d[119]), "+f"(d[120]), "+f"(d[121]), "+f"(d[122]), "+f"(d[123]), "+f"(d[124]), "+f"(d[125]), "+f"(d[126]), "+f"(d[127]) : "r"(a0), "r"(a1), "r"(a2), "r"(a3), "r"(blo));
}
__device__ __forceinline__ void wg_rs128(float (&d)[64], const uint32_t* a, uint32_t blo, uint32_t sc) {
  asm volatile("{\n.reg .pred p;\n.reg .b64 db;\nmov.b64 db, {%68, 0x40000040};\nsetp.ne.b32 p, %69, 0;\n"
    "wgmma.mma_async.sync.aligned.m64n128k16.f32.bf16.bf16 {%0, %1, %2, %3, %4, %5, %6, %7, %8, %9, %10, %11, %12, %13, %14, %15, %16, %17, %18, %19, %20, %21, %22, %23, %24, %25, %26, %27, %28, %29, %30, %31, %32, %33, %34, %35, %36, %37, %38, %39, %40, %41, %42, %43, %44, %45, %46, %47, %48, %49, %50, %51, %52, %53, %54, %55, %56, %57, %58, %59, %60, %61, %62, %63}, {%64,%65,%66,%67}, db, p, 1, 1, 1;\n}\n"
    : "+f"(d[0]), "+f"(d[1]), "+f"(d[2]), "+f"(d[3]), "+f"(d[4]), "+f"(d[5]), "+f"(d[6]), "+f"(d[7]), "+f"(d[8]), "+f"(d[9]), "+f"(d[10]), "+f"(d[11]), "+f"(d[12]), "+f"(d[13]), "+f"(d[14]), "+f"(d[15]), "+f"(d[16]), "+f"(d[17]), "+f"(d[18]), "+f"(d[19]), "+f"(d[20]), "+f"(d[21]), "+f"(d[22]), "+f"(d[23]), "+f"(d[24]), "+f"(d[25]), "+f"(d[26]), "+f"(d[27]), "+f"(d[28]), "+f"(d[29]), "+f"(d[30]), "+f"(d[31]), "+f"(d[32]), "+f"(d[33]), "+f"(d[34]), "+f"(d[35]), "+f"(d[36]), "+f"(d[37]), "+f"(d[38]), "+f"(d[39]), "+f"(d[40]), "+f"(d[41]), "+f"(d[42]), "+f"(d[43]), "+f"(d[44]), "+f"(d[45]), "+f"(d[46]), "+f"(d[47]), "+f"(d[48]), "+f"(d[49]), "+f"(d[50]), "+f"(d[51]), "+f"(d[52]), "+f"(d[53]), "+f"(d[54]), "+f"(d[55]), "+f"(d[56]), "+f"(d[57]), "+f"(d[58]), "+f"(d[59]), "+f"(d[60]), "+f"(d[61]), "+f"(d[62]), "+f"(d[63]) : "r"(a[0]), "r"(a[1]), "r"(a[2]), "r"(a[3]), "r"(blo), "r"(sc));
}
template<int OFF, int SC> __device__ __forceinline__ void wg_rs32(float (&d)[64], const uint32_t* a, uint32_t blo);
template<> __device__ __forceinline__ void wg_rs32<0,0>(float (&d)[64], const uint32_t* a, uint32_t blo) {
  asm volatile("{\n.reg .pred p;\n.reg .b64 db;\nmov.b64 db, {%20, 8};\nsetp.ne.b32 p, 0, 0;\n"
    "wgmma.mma_async.sync.aligned.m64n32k16.f32.bf16.bf16 {%0, %1, %2, %3, %4, %5, %6, %7, %8, %9, %10, %11, %12, %13, %14, %15}, {%16,%17,%18,%19}, db, p, 1, 1, 0;\n}\n"
    : "+f"(d[0]), "+f"(d[1]), "+f"(d[2]), "+f"(d[3]), "+f"(d[4]), "+f"(d[5]), "+f"(d[6]), "+f"(d[7]), "+f"(d[8]), "+f"(d[9]), "+f"(d[10]), "+f"(d[11]), "+f"(d[12]), "+f"(d[13]), "+f"(d[14]), "+f"(d[15]) : "r"(a[0]), "r"(a[1]), "r"(a[2]), "r"(a[3]), "r"(blo));
}
template<> __device__ __forceinline__ void wg_rs32<0,1>(float (&d)[64], const uint32_t* a, uint32_t blo) {
  asm volatile("{\n.reg .pred p;\n.reg .b64 db;\nmov.b64 db, {%20, 8};\nsetp.ne.b32 p, 1, 0;\n"
    "wgmma.mma_async.sync.aligned.m64n32k16.f32.bf16.bf16 {%0, %1, %2, %3, %4, %5, %6, %7, %8, %9, %10, %11, %12, %13, %14, %15}, {%16,%17,%18,%19}, db, p, 1, 1, 0;\n}\n"
    : "+f"(d[0]), "+f"(d[1]), "+f"(d[2]), "+f"(d[3]), "+f"(d[4]), "+f"(d[5]), "+f"(d[6]), "+f"(d[7]), "+f"(d[8]), "+f"(d[9]), "+f"(d[10]), "+f"(d[11]), "+f"(d[12]), "+f"(d[13]), "+f"(d[14]), "+f"(d[15]) : "r"(a[0]), "r"(a[1]), "r"(a[2]), "r"(a[3]), "r"(blo));
}
template<> __device__ __forceinline__ void wg_rs32<16,0>(float (&d)[64], const uint32_t* a, uint32_t blo) {
  asm volatile("{\n.reg .pred p;\n.reg .b64 db;\nmov.b64 db, {%20, 8};\nsetp.ne.b32 p, 0, 0;\n"
    "wgmma.mma_async.sync.aligned.m64n32k16.f32.bf16.bf16 {%0, %1, %2, %3, %4, %5, %6, %7, %8, %9, %10, %11, %12, %13, %14, %15}, {%16,%17,%18,%19}, db, p, 1, 1, 0;\n}\n"
    : "+f"(d[16]), "+f"(d[17]), "+f"(d[18]), "+f"(d[19]), "+f"(d[20]), "+f"(d[21]), "+f"(d[22]), "+f"(d[23]), "+f"(d[24]), "+f"(d[25]), "+f"(d[26]), "+f"(d[27]), "+f"(d[28]), "+f"(d[29]), "+f"(d[30]), "+f"(d[31]) : "r"(a[0]), "r"(a[1]), "r"(a[2]), "r"(a[3]), "r"(blo));
}
template<> __device__ __forceinline__ void wg_rs32<16,1>(float (&d)[64], const uint32_t* a, uint32_t blo) {
  asm volatile("{\n.reg .pred p;\n.reg .b64 db;\nmov.b64 db, {%20, 8};\nsetp.ne.b32 p, 1, 0;\n"
    "wgmma.mma_async.sync.aligned.m64n32k16.f32.bf16.bf16 {%0, %1, %2, %3, %4, %5, %6, %7, %8, %9, %10, %11, %12, %13, %14, %15}, {%16,%17,%18,%19}, db, p, 1, 1, 0;\n}\n"
    : "+f"(d[16]), "+f"(d[17]), "+f"(d[18]), "+f"(d[19]), "+f"(d[20]), "+f"(d[21]), "+f"(d[22]), "+f"(d[23]), "+f"(d[24]), "+f"(d[25]), "+f"(d[26]), "+f"(d[27]), "+f"(d[28]), "+f"(d[29]), "+f"(d[30]), "+f"(d[31]) : "r"(a[0]), "r"(a[1]), "r"(a[2]), "r"(a[3]), "r"(blo));
}
template<> __device__ __forceinline__ void wg_rs32<32,0>(float (&d)[64], const uint32_t* a, uint32_t blo) {
  asm volatile("{\n.reg .pred p;\n.reg .b64 db;\nmov.b64 db, {%20, 8};\nsetp.ne.b32 p, 0, 0;\n"
    "wgmma.mma_async.sync.aligned.m64n32k16.f32.bf16.bf16 {%0, %1, %2, %3, %4, %5, %6, %7, %8, %9, %10, %11, %12, %13, %14, %15}, {%16,%17,%18,%19}, db, p, 1, 1, 0;\n}\n"
    : "+f"(d[32]), "+f"(d[33]), "+f"(d[34]), "+f"(d[35]), "+f"(d[36]), "+f"(d[37]), "+f"(d[38]), "+f"(d[39]), "+f"(d[40]), "+f"(d[41]), "+f"(d[42]), "+f"(d[43]), "+f"(d[44]), "+f"(d[45]), "+f"(d[46]), "+f"(d[47]) : "r"(a[0]), "r"(a[1]), "r"(a[2]), "r"(a[3]), "r"(blo));
}
template<> __device__ __forceinline__ void wg_rs32<32,1>(float (&d)[64], const uint32_t* a, uint32_t blo) {
  asm volatile("{\n.reg .pred p;\n.reg .b64 db;\nmov.b64 db, {%20, 8};\nsetp.ne.b32 p, 1, 0;\n"
    "wgmma.mma_async.sync.aligned.m64n32k16.f32.bf16.bf16 {%0, %1, %2, %3, %4, %5, %6, %7, %8, %9, %10, %11, %12, %13, %14, %15}, {%16,%17,%18,%19}, db, p, 1, 1, 0;\n}\n"
    : "+f"(d[32]), "+f"(d[33]), "+f"(d[34]), "+f"(d[35]), "+f"(d[36]), "+f"(d[37]), "+f"(d[38]), "+f"(d[39]), "+f"(d[40]), "+f"(d[41]), "+f"(d[42]), "+f"(d[43]), "+f"(d[44]), "+f"(d[45]), "+f"(d[46]), "+f"(d[47]) : "r"(a[0]), "r"(a[1]), "r"(a[2]), "r"(a[3]), "r"(blo));
}
template<> __device__ __forceinline__ void wg_rs32<48,0>(float (&d)[64], const uint32_t* a, uint32_t blo) {
  asm volatile("{\n.reg .pred p;\n.reg .b64 db;\nmov.b64 db, {%20, 8};\nsetp.ne.b32 p, 0, 0;\n"
    "wgmma.mma_async.sync.aligned.m64n32k16.f32.bf16.bf16 {%0, %1, %2, %3, %4, %5, %6, %7, %8, %9, %10, %11, %12, %13, %14, %15}, {%16,%17,%18,%19}, db, p, 1, 1, 0;\n}\n"
    : "+f"(d[48]), "+f"(d[49]), "+f"(d[50]), "+f"(d[51]), "+f"(d[52]), "+f"(d[53]), "+f"(d[54]), "+f"(d[55]), "+f"(d[56]), "+f"(d[57]), "+f"(d[58]), "+f"(d[59]), "+f"(d[60]), "+f"(d[61]), "+f"(d[62]), "+f"(d[63]) : "r"(a[0]), "r"(a[1]), "r"(a[2]), "r"(a[3]), "r"(blo));
}
template<> __device__ __forceinline__ void wg_rs32<48,1>(float (&d)[64], const uint32_t* a, uint32_t blo) {
  asm volatile("{\n.reg .pred p;\n.reg .b64 db;\nmov.b64 db, {%20, 8};\nsetp.ne.b32 p, 1, 0;\n"
    "wgmma.mma_async.sync.aligned.m64n32k16.f32.bf16.bf16 {%0, %1, %2, %3, %4, %5, %6, %7, %8, %9, %10, %11, %12, %13, %14, %15}, {%16,%17,%18,%19}, db, p, 1, 1, 0;\n}\n"
    : "+f"(d[48]), "+f"(d[49]), "+f"(d[50]), "+f"(d[51]), "+f"(d[52]), "+f"(d[53]), "+f"(d[54]), "+f"(d[55]), "+f"(d[56]), "+f"(d[57]), "+f"(d[58]), "+f"(d[59]), "+f"(d[60]), "+f"(d[61]), "+f"(d[62]), "+f"(d[63]) : "r"(a[0]), "r"(a[1]), "r"(a[2]), "r"(a[3]), "r"(blo));
}

struct Params {
  const __nv_bfloat16 *k, *v, *h;
  Scratch* s;
  const __nv_bfloat16 *shift, *dv, *x, *w1, *b1, *b2;
  __nv_bfloat16* out;
};
#define DBG(b) false

__device__ __forceinline__ void mma16816(float (&c)[4], uint32_t a0, uint32_t a1, uint32_t a2, uint32_t a3, uint32_t b0, uint32_t b1) {
  asm("mma.sync.aligned.m16n8k16.row.col.f32.bf16.bf16.f32 {%0,%1,%2,%3}, {%4,%5,%6,%7}, {%8,%9}, {%0,%1,%2,%3};"
               : "+f"(c[0]), "+f"(c[1]), "+f"(c[2]), "+f"(c[3]) : "r"(a0), "r"(a1), "r"(a2), "r"(a3), "r"(b0), "r"(b1));
}
__device__ __forceinline__ void ln_rows(uint32_t src, uint32_t stat, int lane) {
  const int g = lane >> 2, t4 = lane & 3;
  uint32_t a = src + g * 1280 + t4 * 16 + (g & 1) * 64, b = a ^ 64;
  asm volatile("" : "+r"(a), "+r"(b) :: "memory");
  const uint32_t one = 0x3F803F80u;
  float s0[4] = {0.f, 0.f, 0.f, 0.f}, s1[4] = {0.f, 0.f, 0.f, 0.f};
#pragma unroll
  for (int j = 0; j < 20; j++) {
    const uint4 u = lds128_ro(((j & 1) ? b : a) + (j >> 1) * 128), v = lds128_ro(((j & 1) ? b : a) + 8 * 1280 + (j >> 1) * 128);
    mma16816(s0, u.x, v.x, u.y, v.y, one, one);
    mma16816(s1, u.z, v.z, u.w, v.w, one, one);
  }
  const float m0 = (s0[0] + s1[0]) * (1.f / D_), m1 = (s0[2] + s1[2]) * (1.f / D_);
  const uint32_t p0 = pack2(m0, m0), p1 = pack2(m1, m1);
  float q0[4] = {0.f, 0.f, 0.f, 0.f}, q1[4] = {0.f, 0.f, 0.f, 0.f}, q2[4] = {0.f, 0.f, 0.f, 0.f}, q3[4] = {0.f, 0.f, 0.f, 0.f};
  s0[0] = s0[1] = s0[2] = s0[3] = s1[0] = s1[1] = s1[2] = s1[3] = 0.f;
  asm volatile("" : "+r"(a), "+r"(b) :: "memory");
#pragma unroll 4
  for (int j = 0; j < 20; j++) {
    uint4 u = lds128_ro(((j & 1) ? b : a) + (j >> 1) * 128), v = lds128_ro(((j & 1) ? b : a) + 8 * 1280 + (j >> 1) * 128);
    u.x = hsub2(u.x, p0); u.y = hsub2(u.y, p0); u.z = hsub2(u.z, p0); u.w = hsub2(u.w, p0);
    v.x = hsub2(v.x, p1); v.y = hsub2(v.y, p1); v.z = hsub2(v.z, p1); v.w = hsub2(v.w, p1);
    mma16816(q0, u.x, v.x, u.y, v.y, u.x, u.y);
    mma16816(q1, u.x, v.x, u.y, v.y, v.x, v.y);
    mma16816(q2, u.z, v.z, u.w, v.w, u.z, u.w);
    mma16816(q3, u.z, v.z, u.w, v.w, v.z, v.w);
    mma16816(s0, u.x, v.x, u.y, v.y, one, one);
    mma16816(s1, u.z, v.z, u.w, v.w, one, one);
  }
  if (t4 == (g >> 1)) {
    const float r0 = (s0[0] + s1[0]) * (1.f / D_), r1 = (s0[2] + s1[2]) * (1.f / D_);
    const float v0 = ((g & 1) ? q0[1] + q2[1] : q0[0] + q2[0]) * (1.f / D_) - r0 * r0;
    const float v1 = ((g & 1) ? q1[3] + q3[3] : q1[2] + q3[2]) * (1.f / D_) - r1 * r1;
    asm volatile("st.shared.v2.f32 [%0], {%1,%2};" :: "r"(stat + g * 8), "f"(m0), "f"(rsqrt_fast(fmaxf(v0, 0.f) + 1e-5f)) : "memory");
    asm volatile("st.shared.v2.f32 [%0], {%1,%2};" :: "r"(stat + g * 8 + 64), "f"(m1), "f"(rsqrt_fast(fmaxf(v1, 0.f) + 1e-5f)) : "memory");
  }
}

struct KvJob { uint2 kk[11], vv[8]; uint4 s0, s1; };
__device__ __forceinline__ void kv_load(const Params& P, int unit, int lane, KvJob& J) {
  const int t0 = (unit & 127) * 16 + (lane >> 4) * 8, c = (unit >> 7) * 64 + (lane & 15) * 4;
  const __nv_bfloat16* kp = P.k + (size_t)t0 * D_ + c;
  const __nv_bfloat16* vp = P.v + (size_t)t0 * D_ + c;
#pragma unroll
  for (int j = 0; j < 11; j++) { J.kk[j] = make_uint2(0u, 0u); if (j >= 3 || t0 > 0) J.kk[j] = ldg64(kp + (j - 3) * D_); }
#pragma unroll
  for (int j = 0; j < 8; j++) J.vv[j] = ldg64(vp + j * D_);
  J.s0 = __ldg((const uint4*)(P.shift + c * 4)); J.s1 = __ldg((const uint4*)(P.shift + c * 4 + 8));
}
template <bool LOCAL> __device__ __forceinline__ void kv_finish(const KvJob& J, uint8_t* o, uint32_t a, int d1, int d2, int d3) {
  const uint32_t wa[4] = {__byte_perm(J.s0.x, J.s0.z, 0x5410), __byte_perm(J.s0.x, J.s0.z, 0x7632), __byte_perm(J.s0.y, J.s0.w, 0x5410), __byte_perm(J.s0.y, J.s0.w, 0x7632)};
  const uint32_t wb[4] = {__byte_perm(J.s1.x, J.s1.z, 0x5410), __byte_perm(J.s1.x, J.s1.z, 0x7632), __byte_perm(J.s1.y, J.s1.w, 0x5410), __byte_perm(J.s1.y, J.s1.w, 0x7632)};
  uint32_t ra[8], rb[8];
#pragma unroll
  for (int j = 0; j < 8; j++) {
    ra[j] = hmul2(hfma2(J.kk[j + 3].x, wa[0], hfma2(J.kk[j + 2].x, wa[1], hfma2(J.kk[j + 1].x, wa[2], hmul2(J.kk[j].x, wa[3])))), J.vv[j].x);
    rb[j] = hmul2(hfma2(J.kk[j + 3].y, wb[0], hfma2(J.kk[j + 2].y, wb[1], hfma2(J.kk[j + 1].y, wb[2], hmul2(J.kk[j].y, wb[3])))), J.vv[j].y);
  }
  const uint32_t* src[4] = {ra, ra, rb, rb};
  const int off[4] = {0, d1, d2, d3};
#pragma unroll
  for (int c = 0; c < 4; c++) {
    const uint32_t sel = (c & 1) ? 0x7632 : 0x5410, *r = src[c];
    const uint32_t w0 = __byte_perm(r[7], r[6], sel), w1 = __byte_perm(r[5], r[4], sel), w2 = __byte_perm(r[3], r[2], sel), w3 = __byte_perm(r[1], r[0], sel);
    if (LOCAL) sts128(a + off[c], w0, w1, w2, w3); else stg128(o + off[c], w0, w1, w2, w3);
  }
}

template <int J> __device__ __forceinline__ void ldp(uint32_t* p, uint32_t pa) {
  p[0] = lds32(pa + 256 * J); p[1] = lds32(pa + 256 * J + 128); p[2] = lds32(pa + 256 * J + 16); p[3] = lds32(pa + 256 * J + 144);
}
template <int J, int BASE> __device__ __forceinline__ void cstep(float (&d)[64], const uint32_t* a, uint32_t db) {
  if (BASE + 96 < 256 - 16 * J) wg_rs32<48, (J != 0)>(d, a, db + (J * 16 + BASE + 96));
  if (BASE + 64 < 256 - 16 * J) wg_rs32<32, (J != 0)>(d, a, db + (J * 16 + BASE + 64));
  if (BASE + 32 < 256 - 16 * J) wg_rs32<16, (J != 0)>(d, a, db + (J * 16 + BASE + 32));
  if (BASE < 256 - 16 * J) wg_rs32<0, (J != 0)>(d, a, db + (J * 16 + BASE));
}
template <int JN> __device__ __forceinline__ void csend(float (&d)[64], uint32_t sa, uint32_t carry, bool sh) {
  constexpr int JL = JN & 15;
  float v0 = d[4 * JL], v1 = d[4 * JL + 1];
  if (JL < 15) { v0 += d[4 * JL + 6]; v1 += d[4 * JL + 7]; }
  uint32_t v = pack2(v0, v1);
  if (JN == 15) v = hadd2(v, carry);
  if (JN == 0) sts32p(sa, v, !sh); else sts32(sa + JN * 128, v);
}
#define CSEND8(B, CARRY) csend<B + 7>(d, sa, CARRY, sh); csend<B + 6>(d, sa, 0, sh); csend<B + 5>(d, sa, 0, sh); csend<B + 4>(d, sa, 0, sh); \
                         csend<B + 3>(d, sa, 0, sh); csend<B + 2>(d, sa, 0, sh); csend<B + 1>(d, sa, 0, sh); csend<B>(d, sa, 0, sh)

__device__ __forceinline__ void conv_issue_u(const Params& P, int ch, uint32_t dst, uint32_t bar, unsigned ep) {
  flag_wait(P.s->cnt, C_KV + (ch >> 6), ep * 128);
  fence_async();
  mbar_expect(bar, 4096);
  bulk_g2s(dst, P.s->ur + (size_t)ch * S_, 4096, bar);
}

struct HJob { uint4 v0, v1; uint32_t n0, n1, dv; };
__device__ __forceinline__ void h_load(const Params& P, int ch, int c0, HJob& H) {
  const __nv_bfloat16* hp = P.h + (size_t)ch * S_ + c0 * 8;
  H.v0 = ldg128(hp); H.v1 = ldg128(hp + 256);
  H.n0 = ldg32(hp + 8); H.n1 = 0;
  if (c0 + 33 < 256) H.n1 = ldg32(hp + 264);
  H.dv = 0;
  if (c0 == 0) asm volatile("ld.global.nc.u16 %0, [%1];" : "=r"(H.dv) : "l"(P.dv + ch));
}
__device__ __forceinline__ void h_store(uint32_t st, int c0, HJob& H) {
  H.v0.x = __byte_perm(pack2(bf_lo(H.v0.x) + bf_lo(H.dv), 0.f), H.v0.x, 0x7610);
  if (c0 == 0) sts128(st + ST_H1, 0, 0, 0, H.v0.x << 16);
  sts128(st + ST_H0 + 16 + 16 * c0, H.v0.x, H.v0.y, H.v0.z, H.v0.w);
  sts128(st + ST_H1 + 16 + 16 * c0, __byte_perm(H.v0.x, H.v0.y, 0x5432), __byte_perm(H.v0.y, H.v0.z, 0x5432), __byte_perm(H.v0.z, H.v0.w, 0x5432), __byte_perm(H.v0.w, H.n0, 0x5432));
  sts128(st + ST_H0 + 528 + 16 * c0, H.v1.x, H.v1.y, H.v1.z, H.v1.w);
  sts128(st + ST_H1 + 528 + 16 * c0, __byte_perm(H.v1.x, H.v1.y, 0x5432), __byte_perm(H.v1.y, H.v1.z, 0x5432), __byte_perm(H.v1.z, H.v1.w, 0x5432), __byte_perm(H.v1.w, H.n1, 0x5432));
}
__device__ __forceinline__ void zero_pads(uint32_t st, int nst, int tid) {
  if (tid < 25 * nst) sts128(st + (tid >= 25 ? ST_BYTES - 400 : 0) + 4096 + tid * 16, 0, 0, 0, 0);
}
__device__ __forceinline__ void zero_xch(uint32_t xa, int l) { sts128(xa + (l >> 3) * 4096 + 3968 + (l & 7) * 16, 0, 0, 0, 0); }

__device__ __forceinline__ void conv_run(const Params& P, int ch0, int ch1, int ch2, int ch3, int nloc, uint32_t ux, int n, uint32_t xa, uint32_t yb, uint32_t st0, int nst, uint32_t ubar,
                                         int barid, unsigned ep, int warp, int lane) {
  const int g = lane >> 2, t4 = lane & 3;
  const int y0 = 16 * warp - 7 + g + 2 * t4;
  const uint32_t poff = (g & 1) ? (ST_H0 + 16 + y0 * 2) : (ST_H1 + 16 + (y0 - 1) * 2);
  const bool sh = t4 < warp;
  const uint32_t sa = xa + warp * 4096 + (lane & ~3) * 4 + (((t4 - warp) & 3) << 2) - (sh ? 128 : 0);
  const uint32_t rb = xa + warp * 1024 + lane * 4;
  const uint32_t ya = yb + (255 - (64 * warp + lane)) * 16;
  const int c0 = warp * 64 + lane;
  float d[64];
  int ch = ch0;
#pragma unroll 1
  for (int m = 0; m < n; m++) {
    const int nch = m == 0 ? ch1 : m == 1 ? ch2 : ch3;
    const int s = m & (nst - 1), s1 = (m + 1) & (nst - 1);
    const uint32_t st = st0 + s * ST_BYTES, st1 = st0 + s1 * ST_BYTES;
    HJob H;
    if (m + 1 < n) h_load(P, nch, c0, H);
    const uint32_t db = (((m == 2 && nloc == 3 ? ux : st + ST_U) & 0x3FFFF) >> 4) | (1u << 16);
    const uint32_t pa = st + poff;
    uint32_t p[32];
    ldp<0>(p, pa); ldp<1>(p + 4, pa); ldp<2>(p + 8, pa); ldp<3>(p + 12, pa);
    if (m < 1 || m >= nloc) mbar_wait(ubar + 8 * s, nst == 2 ? (m == 2) : m & 1);
    if (m == 0 && lane == 0 && warp == 0 && barid == 1) STAMP(9);
    if (m == 0 && lane == 0 && warp == 0 && nst == 1) STAMP(6);
    wg_fence(); cstep<0, 128>(d, p, db); cstep<1, 128>(d, p + 4, db); cstep<2, 128>(d, p + 8, db); cstep<3, 128>(d, p + 12, db); wg_commit();
    ldp<4>(p + 16, pa); ldp<5>(p + 20, pa); ldp<6>(p + 24, pa); ldp<7>(p + 28, pa);
    wg_fence(); cstep<4, 128>(d, p + 16, db); cstep<5, 128>(d, p + 20, db); cstep<6, 128>(d, p + 24, db); cstep<7, 128>(d, p + 28, db); wg_commit();
    wg_wait<1>();
    CSEND8(24, 0);
    wg_wait<0>();
    CSEND8(16, 0);
    const uint32_t carry = pack2(d[2], d[3]);
    wg_fence(); cstep<0, 0>(d, p, db); cstep<1, 0>(d, p + 4, db); cstep<2, 0>(d, p + 8, db); cstep<3, 0>(d, p + 12, db); wg_commit();
    cstep<4, 0>(d, p + 16, db); cstep<5, 0>(d, p + 20, db); cstep<6, 0>(d, p + 24, db); cstep<7, 0>(d, p + 28, db); wg_commit();
    if (warp == 1 && m == 0 && nloc == 2 && elect()) { bulk_wait<0>(); flag_add(P.s->cnt, C_INIT); STAMP(18); }
    if (warp == 0 && elect()) {
      bulk_wait_read<0>();
      if (nst == 2 && m + 1 < n && m + 1 >= nloc) conv_issue_u(P, nch, st1 + ST_U, ubar + 8 * s1, ep);
    }
    wg_wait<1>();
    ldp<8>(p, pa); ldp<9>(p + 4, pa); ldp<10>(p + 8, pa); ldp<11>(p + 12, pa);
    wg_fence(); cstep<8, 0>(d, p, db); cstep<9, 0>(d, p + 4, db); cstep<10, 0>(d, p + 8, db); cstep<11, 0>(d, p + 12, db); wg_commit();
    wg_wait<1>();
    ldp<12>(p + 16, pa); ldp<13>(p + 20, pa); ldp<14>(p + 24, pa); ldp<15>(p + 28, pa);
    wg_fence(); cstep<12, 0>(d, p + 16, db); cstep<13, 0>(d, p + 20, db); cstep<14, 0>(d, p + 24, db); cstep<15, 0>(d, p + 28, db); wg_commit();
    wg_wait<1>();
    CSEND8(8, carry);
    wg_wait<0>();
    CSEND8(0, 0);
    bar_sync(barid, 128);
    if (warp == 0 && nst == 1 && m + 1 < n && elect()) conv_issue_u(P, nch, st + ST_U, ubar, ep);
    uint32_t y[8];
#pragma unroll
    for (int q = 0; q < 8; q++) {
      const uint32_t r0 = lds32(rb + q * 128), r1 = lds32(rb + 4096 + q * 128), r2 = lds32(rb + 8192 + q * 128), r3 = lds32(rb + 12288 + q * 128);
      y[q] = hadd2(hadd2(r0, r1), hadd2(r2, r3));
    }
    stsm4t(ya, y[0], y[1], y[2], y[3]);
    stsm4t(ya - 512, y[4], y[5], y[6], y[7]);
    if (m + 1 < n) h_store(st1, c0, H);
    fence_async_smem();
    bar_sync(barid, 128);
    if (warp == 0 && elect()) { bulk_s2g(P.s->yt + (size_t)ch * S_, yb, 4096); bulk_commit(); }
    ch = nch;
    if (warp == 0 && lane == 0 && nst == 2 && barid == 1) STAMP(22 + m);
    if (warp == 0 && lane == 0 && nst == 2 && barid == 3) STAMP(12 + m);
    if (warp == 0 && lane == 0 && nst == 1 && m == 0) STAMP(7);
  }
  if (warp == 0) {
    if (elect()) { bulk_wait<0>(); fence_gpu(); }
    __syncwarp();
    if (lane < n) flag_add_relaxed(P.s->cnt, C_Y + ((lane == 0 ? ch0 : lane == 1 ? ch1 : lane == 2 ? ch2 : ch3) >> 7));
  }
}

__global__ void __cluster_dims__(2, 1, 1) __launch_bounds__(NTHR, 1)
fused_kernel(const Params P, const __grid_constant__ CUtensorMap tm_x, const __grid_constant__ CUtensorMap tm_x64,
             const __grid_constant__ CUtensorMap tm_w1, const __grid_constant__ CUtensorMap tm_w2,
             const __grid_constant__ CUtensorMap tm_out, const __grid_constant__ CUtensorMap tm_yt,
             const __grid_constant__ CUtensorMap tm_k8, const __grid_constant__ CUtensorMap tm_v8) {
  const uint32_t sb = smem_u32(smem_raw);
  const uint32_t bars = sb + OFF_BAR;
  const int wgi = __shfl_sync(~0u, threadIdx.x >> 7, 0), warp = __shfl_sync(~0u, (threadIdx.x >> 5) & 3, 0), lane = threadIdx.x & 31;
  const int cl = blockIdx.x >> 1, rank = blockIdx.x & 1;
  const bool is_conv = cl >= CONV_CL0 && cl < CONV_CL0 + CONV_NCL;
  const int ci = blockIdx.x - 2 * CONV_CL0;
  const int mc = cl < CONV_CL0 ? cl : cl - CONV_NCL;
  const int f = mc >> 3, mt = 2 * (mc & 7) + rank;
  const int mi = 2 * mc + rank;
  if (threadIdx.x == 0) STAMP(0);

  if (wgi == 1 && warp == 3) asm volatile("prefetch.global.L2 [%0];" :: "l"(lane < 10 ? P.b2 + lane * 64 : P.b1 + (lane - 10) * 64));
  if (wgi == 0 && warp == 0 && elect()) {
    mbar_init(bars + 8 * B_WF, 1);
    if (!is_conv && !DBG(1)) {
      mbar_expect(bars + 8 * B_WF, 49152);
      tma_ld(sb + OFF_X, &tm_x, 0, mt * 128, bars + 8 * B_WF);
      tma_ld3(sb + OFF_W, &tm_w1, 0, f * 4, bars + 8 * B_WF);
      tma_ld3(sb + OFF_W + 16384, &tm_w1, 0, f * 4 + 2, bars + 8 * B_WF);
    }
    if (is_conv) {
      mbar_init(bars + 8 * (B_KV + 1), 1); mbar_init(bars + 8 * B_LN, 1);
      const int p0 = ci * 3 < 52 ? 30 * ci : 52 + 27 * ci, p1 = ci * 3 + 3 < 52 ? 30 * ci + 30 : 52 + 27 * ci + 27;
      mbar_expect(bars + 8 * B_LN, (p1 - p0) * 2560);
      bulk_g2s(sb + CV_LN, P.x + (size_t)p0 * 2 * D_, (p1 - p0) * 2560, bars + 8 * B_LN);
      mbar_expect(bars + 8 * B_KV, 32768);
      tma_ld3x(sb, &tm_k8, ci * 8, 0, bars + 8 * B_KV);
      tma_ld3x(sb + 32768, &tm_v8, ci * 8, 0, bars + 8 * B_KV);
      mbar_expect(bars + 8 * (B_KV + 1), 32768);
      tma_ld3x(sb + 16384, &tm_k8, ci * 8, 128, bars + 8 * (B_KV + 1));
      tma_ld3x(sb + 49152, &tm_v8, ci * 8, 128, bars + 8 * (B_KV + 1));
    }
#pragma unroll
    for (int b = 1; b < B_NUM; b++) if (b > B_LN || !is_conv) mbar_init(bars + 8 * b, (b >= B_WE && b < B_BEXT) || b == B_Z ? 4 : b == B_XT ? 2 : 1);
  }
  asm volatile("fence.mbarrier_init.release.cluster;" ::: "memory");
  __syncthreads();
  if (threadIdx.x == 0) STAMP(1);
  cluster_arrive();
  if (DBG(1) && !is_conv) { cluster_wait(); DUMP(); return; }
  if (DBG(4) && (is_conv || wgi == 2)) { cluster_wait(); if (!is_conv) bar_sync(6, 384); return; }

  if (is_conv || wgi == 2) {
    const int tid = warp * 32 + lane;
    const uint32_t xa = is_conv ? sb + CV_X + wgi * 16384 : sb + OFF_C, yb = is_conv ? sb + CV_Y + wgi * 4096 : xa + 16384;
    const uint32_t st0 = is_conv ? sb + CV_ST + wgi * 2 * ST_BYTES : xa + 20480, ubar = bars + 8 * (B_U + (is_conv ? 2 * wgi : 0));
    const int ch0 = is_conv ? ci * 8 + wgi : 432 + mi;
    const int ch1 = is_conv ? ch0 + 3 : ch0 + 96, ch2 = is_conv ? (wgi < 2 ? ch0 + 6 : 288 + ci) : ch0 + 112, ch3 = 324 + 3 * ci + wgi;
    zero_pads(st0, is_conv ? 2 : 1, tid);
    if (is_conv && wgi == 2 && tid >= 64 && tid < 112) sts128(sb + CV_UX + (tid >= 88 ? ST_H0 - 384 : 0) + 4096 + (tid - 64) * 16, 0, 0, 0, 0);
    if (!is_conv && warp == 2) zero_xch(xa, lane);
    fence_async_smem();
    unsigned ep;
    asm volatile("ld.relaxed.gpu.global.u32 %0, [%1];" : "=r"(ep) : "l"(P.s->cnt + C_EPOCH * 32) : "memory");
    HJob H;
    KvJob K, K1;
    const int unit = 512 + warp * 96 + mi;
    if (is_conv) {
      const int p0 = ci * 3 < 52 ? 30 * ci : 52 + 27 * ci, p1 = ci * 3 + 3 < 52 ? 30 * ci + 30 : 52 + 27 * ci + 27;
      h_load(P, ch0, warp * 64 + lane, H);
      if (wgi < 2) {
        K.s0 = __ldg((const uint4*)(P.shift + ci * 32)); K.s1 = __ldg((const uint4*)(P.shift + ci * 32 + 8));
        K1.s0 = __ldg((const uint4*)(P.shift + ci * 32 + 16)); K1.s1 = __ldg((const uint4*)(P.shift + ci * 32 + 24));
        h_store(st0, warp * 64 + lane, H);
        ep = __shfl_sync(~0u, ep, 0) + 1;
        mbar_wait(bars + 8 * B_KV, 0);
        if (wgi) mbar_wait(bars + 8 * (B_KV + 1), 0);
        if (tid == 0) STAMP(20 + wgi);
        const uint32_t ka = sb + wgi * 16384 + tid * 16, kp = tid ? ka - 16 : sb + 127 * 16;
#pragma unroll
        for (int j = 0; j < 11; j++) {
          uint4 t = lds128(j < 3 ? kp + (5 + j) * 2048 : ka + (j - 3) * 2048);
          if (j < 3 && tid + wgi == 0) t = make_uint4(0u, 0u, 0u, 0u);
          K.kk[j] = make_uint2(t.x, t.y); K1.kk[j] = make_uint2(t.z, t.w);
        }
#pragma unroll
        for (int j = 0; j < 8; j++) { const uint4 t = lds128(ka + 32768 + j * 2048); K.vv[j] = make_uint2(t.x, t.y); K1.vv[j] = make_uint2(t.z, t.w); }
        const uint32_t ua = sb + CV_ST + (255 - wgi * 128 - tid) * 16;
        kv_finish<true>(K, nullptr, ua, 2 * ST_BYTES, 4 * ST_BYTES, ST_BYTES);
        kv_finish<true>(K1, nullptr, ua + 3 * ST_BYTES, 2 * ST_BYTES, CV_UX - CV_ST - 3 * ST_BYTES, CV_UX - CV_ST - 3 * ST_BYTES + ST_H0);
        fence_async_smem();
        bar_sync(11, 256);
        if (wgi == 1 && warp < 3) zero_xch(sb + CV_X + warp * 16384, lane);
        bar_sync(10, 384);
        if (tid < 3 && wgi == 0) mbar_arrive(bars + 8 * (B_U + 2 * tid));
      } else {
        h_store(st0, warp * 64 + lane, H);
        ep = __shfl_sync(~0u, ep, 0) + 1;
        mbar_wait(bars + 8 * B_LN, 0);
        if (tid == 0) STAMP(30);
        ln_rows(sb + CV_LN + warp * 16 * 1280, sb + OFF_STAT + warp * 128, lane);
        fence_async_smem();
        bar_arrive(10, 384);
        bar_sync(1 + wgi, 128);
        if (tid == 0) STAMP(17);
        if (warp == 0) {
          if (elect()) { bulk_s2g(P.s->stats + 2 * p0, sb + OFF_STAT, (p1 - p0) * 16); bulk_commit(); bulk_wait<0>(); fence_gpu(); }
          __syncwarp();
          if (p0 + lane < p1) flag_add_relaxed(P.s->cnt, C_LN + ((p0 + lane) >> 6));
          if (lane == 0) STAMP(31);
        }
        if (warp == 1) {
          if (elect()) { bulk_s2g(P.out + (size_t)p0 * 2 * D_, sb + CV_LN, (p1 - p0) * 2560); bulk_commit(); }
          __syncwarp();
        }
      }
      if (tid == 0) STAMP(2 + wgi);
    } else {
      {
        const __nv_bfloat16* wp = P.w1 + (size_t)(mt * 40 + warp * 10) * F_ + f * 256 + lane * 8;
        uint4 w[10];
#pragma unroll
        for (int j = 0; j < 10; j++) w[j] = ldg128(DBG(32) ? P.b1 : wp + j * F_);
        float a[8] = {0.f, 0.f, 0.f, 0.f, 0.f, 0.f, 0.f, 0.f};
#pragma unroll
        for (int j = 0; j < 10; j++) {
          a[0] += bf_lo(w[j].x); a[1] += bf_hi(w[j].x); a[2] += bf_lo(w[j].y); a[3] += bf_hi(w[j].y);
          a[4] += bf_lo(w[j].z); a[5] += bf_hi(w[j].z); a[6] += bf_lo(w[j].w); a[7] += bf_hi(w[j].w);
        }
        ep = __shfl_sync(~0u, ep, 0) + 1;
        if (tid == 0 && a[0] != 1.2345f) STAMP(9);
        if (warp < 3) {
          sts128(yb + warp * 1024 + lane * 16, __float_as_uint(a[0]), __float_as_uint(a[1]), __float_as_uint(a[2]), __float_as_uint(a[3]));
          sts128(yb + warp * 1024 + 512 + lane * 16, __float_as_uint(a[4]), __float_as_uint(a[5]), __float_as_uint(a[6]), __float_as_uint(a[7]));
          bar_arrive(1 + wgi, 128);
        } else {
          bar_sync(1 + wgi, 128);
#pragma unroll
          for (int j = 0; j < 3; j++) {
            const float4 t0 = lds128f(yb + j * 1024 + lane * 16), t1 = lds128f(yb + j * 1024 + 512 + lane * 16);
            a[0] += t0.x; a[1] += t0.y; a[2] += t0.z; a[3] += t0.w; a[4] += t1.x; a[5] += t1.y; a[6] += t1.z; a[7] += t1.w;
          }
          float* cp = P.s->cs + ((ep & 1) * 2 + rank) * F_ + f * 256 + lane * 8;
          red4f(cp, a[0], a[1], a[2], a[3]); red4f(cp + 4, a[4], a[5], a[6], a[7]);
          __syncwarp();
          if (lane == 0) { flag_add(P.s->cnt, C_CS + f); STAMP(30); }
          __syncwarp();
        const uint4 b = __ldg((const uint4*)(P.b1 + f * 256 + lane * 8));
        if (lane < 2) flag_wait(P.s->cnt, lane ? C_LN + mt : C_CS + f, ep * (lane ? 64 : 16));
        __syncwarp();
        const float* cq = P.s->cs + (ep & 1) * 2 * F_ + f * 256 + lane * 8;
        const float4 u0 = ldcg128f(cq), u1 = ldcg128f(cq + 4), u2 = ldcg128f(cq + F_), u3 = ldcg128f(cq + F_ + 4);
        const float4 t0 = ldcg128f(&P.s->stats[mt * 128 + lane * 2]), t1 = ldcg128f(&P.s->stats[mt * 128 + 64 + lane * 2]);
        const float c[8] = {-u0.x - u2.x, -u0.y - u2.y, -u0.z - u2.z, -u0.w - u2.w, -u1.x - u3.x, -u1.y - u3.y, -u1.z - u3.z, -u1.w - u3.w};
        uint32_t hi[4], lo[4];
#pragma unroll
        for (int j = 0; j < 4; j++) {
          hi[j] = pack2(c[2 * j], c[2 * j + 1]);
          lo[j] = pack2(c[2 * j] - bf_lo(hi[j]), c[2 * j + 1] - bf_hi(hi[j]));
        }
        const uint32_t ba = xa + (lane >> 3) * 2048;
        const int l7 = lane & 7;
        sts128(ba + 0 * 128 + ((l7 ^ 0) << 4), hi[0], hi[1], hi[2], hi[3]);
        sts128(ba + 1 * 128 + ((l7 ^ 1) << 4), lo[0], lo[1], lo[2], lo[3]);
        sts128(ba + 2 * 128 + ((l7 ^ 2) << 4), hi[0], hi[1], hi[2], hi[3]);
        sts128(ba + 3 * 128 + ((l7 ^ 3) << 4), b.x, b.y, b.z, b.w);
        sts128(ba + 4 * 128 + ((l7 ^ 4) << 4), b.x, b.y, b.z, b.w);
        sts128(ba + 5 * 128 + ((l7 ^ 5) << 4), lo[0], lo[1], lo[2], lo[3]);
#pragma unroll
        for (int r = 6; r < 16; r++) sts128(ba + r * 128 + (l7 << 4), 0, 0, 0, 0);
        sts128(sb + OFF_STAT + lane * 16, __float_as_uint(t0.x), __float_as_uint(t0.y), __float_as_uint(t0.z), __float_as_uint(t0.w));
        sts128(sb + OFF_STAT + 512 + lane * 16, __float_as_uint(t1.x), __float_as_uint(t1.y), __float_as_uint(t1.z), __float_as_uint(t1.w));
        fence_async_smem();
        __syncwarp();
        if (lane == 0) { mbar_arrive(bars + 8 * B_BEXT); STAMP(3); }
        }
      }
      kv_load(P, DBG(64) ? 0 : unit, lane, K);
      kv_load(P, DBG(64) ? 0 : unit + 384, lane, K1);
      h_load(P, ch0, warp * 64 + lane, H);
#pragma unroll 1
      for (int r = 0; r < 2; r++) {
        const int u = unit + 384 * r;
        kv_finish<false>(K, (uint8_t*)(P.s->ur + (size_t)((u >> 7) * 64 + (lane & 15) * 4) * S_ + (S_ - 8 - (u & 127) * 16 - (lane >> 4) * 8)), 0, S_ * 2, S_ * 4, S_ * 6);
        K = K1;
      }
      if (tid == 0) STAMP(29);
      fence_async();
      __syncwarp();
      if (lane == 0) { fence_gpu(); flag_add_relaxed(P.s->cnt, C_KV + (unit >> 7)); flag_add_relaxed(P.s->cnt, C_KV + 3 + (unit >> 7)); }
      __syncwarp();
      if (tid == 0) STAMP(31);
      h_store(st0, warp * 64 + lane, H);
      if (warp == 0 && elect()) {
        map_prefetch(&tm_out); map_prefetch(&tm_yt); map_prefetch(&tm_x64);
        conv_issue_u(P, ch0, st0 + ST_U, ubar, ep);
      }
      if (warp == 1 && mi == 0) {
#pragma unroll 1
        for (int i = lane; i < F_ / 2; i += 32) ((float4*)(P.s->cs + ((ep + 1) & 1) * 2 * F_))[i] = make_float4(0.f, 0.f, 0.f, 0.f);
      }
      if (warp == 2 && lane == 0) { flag_wait(P.s->cnt, C_INIT, ep * 36); mbar_arrive(bars + 8 * B_INIT); }
      if (tid == 0) STAMP(2);
      bar_sync(6, 384);
    }
    cluster_wait();
    if (DBG(3)) { mbar_wait(ubar, 0); if (tid == 0 && wgi == 0) STAMP(9); DUMP(); return; }
    conv_run(P, ch0, ch1, ch2, ch3, is_conv ? (wgi < 2 ? 3 : 2) : 0, sb + CV_UX + wgi * ST_H0, is_conv ? 4 : (f == 5 ? 3 : 2), xa, yb, st0,
             is_conv ? 2 : 1, ubar, 1 + wgi, ep, warp, lane);
    if (tid == 0) STAMP(6 + wgi);
    if (!is_conv && f < 5) {
      const int g = lane >> 2, l7 = lane & 7;
      const uint32_t sp = sb + OFF_STAT + (warp * 32 + g) * 8;
      const float2 s0 = lds64f(sp), s1 = lds64f(sp + 64), s2 = lds64f(sp + 128), s3 = lds64f(sp + 192);
      bar_sync(1 + wgi, 128);
      if (warp == 0 && elect()) {
        flag_wait(P.s->cnt, C_Y + f, ep * 128);
        fence_async();
        mbar_expect(bars + 8 * B_Y, 32768);
        tma_ld(sb + OFF_C, &tm_yt, mt * 128, f * 128, bars + 8 * B_Y);
        tma_ld(sb + OFF_C + 16384, &tm_yt, mt * 128 + 64, f * 128, bars + 8 * B_Y);
        STAMP(10);
      }
      uint32_t ma = pack2(s0.x, s0.x), ra = pack2(s0.y, s0.y), mb = pack2(s1.x, s1.x), rb = pack2(s1.y, s1.y);
      uint32_t xa = sb + OFF_X + (warp >> 1) * 32768 + (32 * (warp & 1) + l7 + (lane & 8)) * 128;
      uint32_t ya = sb + OFF_C + (warp >> 1) * 16384 + (8 * (lane >> 4) + l7) * 128;
      int tc = 4 * (warp & 1) + ((lane >> 3) & 1);
      uint32_t bb[16];
#pragma unroll
      for (int j = 0; j < 16; j++) bb[j] = ldg32(P.b2 + f * 128 + (lane & 3) * 2 + j * 8);
      mbar_wait(bars + 8 * B_XT, 0);
      mbar_wait(bars + 8 * B_Y, 0);
#pragma unroll 1
      for (int sl = 0; sl < 2; sl++) {
#pragma unroll
        for (int cp = 0; cp < 8; cp++) {
          uint32_t xr[4], yr[4];
          const uint32_t a = xa + (cp >> 2) * 8192 + (((2 * (cp & 3) + (lane >> 4)) ^ l7) << 4);
          ldsm4(a, xr);
          ldsm4t(ya + cp * 2048 + ((tc ^ l7) << 4), yr);
          const uint32_t b0 = bb[2 * cp], b1 = bb[2 * cp + 1];
          stsm4(a, hfma2(hmul2(hsub2(xr[0], ma), ra), yr[0], b0), hfma2(hmul2(hsub2(xr[1], mb), rb), yr[1], b0),
                   hfma2(hmul2(hsub2(xr[2], ma), ra), yr[2], b1), hfma2(hmul2(hsub2(xr[3], mb), rb), yr[3], b1));
        }
        xa += 2048; tc += 2;
        ma = pack2(s2.x, s2.x); ra = pack2(s2.y, s2.y); mb = pack2(s3.x, s3.x); rb = pack2(s3.y, s3.y);
      }
      __syncwarp();
      if (lane == 0) mbar_arrive(bars + 8 * B_Z);
      if (tid == 0) STAMP(11);
    }
    if (blockIdx.x == NCTA - 1 && tid == 0) {
#pragma unroll 1
      for (int i = 0; i < 5; i++) flag_wait(P.s->cnt, C_Y + i, ep * 128);
      flag_add_relaxed(P.s->cnt, C_EPOCH);
    }
    DUMP();
  } else {
    const int w = wgi, tid = warp * 32 + lane, g = lane >> 2, t4 = lane & 3;
    auto chunk_of = [&](int qi) { int q = f + 1 + qi; return f == 5 ? qi : q >= 5 ? q - 5 : q; };
    auto load_stage = [&](int v) {
      const uint32_t sl = v & 3, fb = bars + 8 * (B_WF + sl), dst = sb + OFF_W + sl * 32768 + rank * 16384;
      if (v >= 4) mbar_wait(bars + 8 * (B_WE + sl), ((v >> 2) - 1) & 1);
      if (elect()) {
        if (v < 10) {
          mbar_expect(fb, 49152);
          tma_ld3_mc(dst, &tm_w1, v * 64, f * 4 + rank * 2, fb);
          tma_ld(sb + OFF_X + sl * 16384, &tm_x, v * 64, mt * 128, fb);
        } else {
          mbar_expect(fb, 32768);
          tma_ld3_mc(dst, &tm_w2, f * 256 + (v & 1) * 128, chunk_of((v - 10) >> 1) * 2 + rank, fb);
        }
      }
      __syncwarp();
    };
    const uint32_t we_l = bars + 8 * B_WE, we_r = mapa(we_l, rank ^ 1);
    auto release = [&](uint32_t sl) { if (warp == 0 && elect()) { mbar_arrive(we_l + 8 * sl); mbar_arrive_cl(we_r + 8 * sl); } };
    cluster_wait();
    if (tid == 0 && w == 1) STAMP(5);
    if (w == 1 && warp == 0) {
#pragma unroll 1
      for (int v = 1; v < 4; v++) { if (v == FIRST_GATE) mbar_wait(bars + 8 * B_WF, 0); load_stage(v); }
    }
    uint32_t hf[64];
    {
      float d[128];
      const uint32_t xlo = ((sb + OFF_X + w * 8192) & 0x3FFFF) >> 4;
      const uint32_t wlo = (((sb + OFF_W) & 0x3FFFF) >> 4) | (512u << 16);
      uint32_t e0 = 0, e1 = 0;
#pragma unroll 1
      for (int v = 0; v < 10; v++) {
        const uint32_t sl = v & 3;
        TK(t1);
        mbar_wait(bars + 8 * (B_WF + sl), (v >> 2) & 1);
        TK(t2);
        if (v == 0 && tid == 0 && w == 0) STAMP(12);
        const uint32_t a = xlo + sl * 1024, b = wlo + sl * 2048;
        wg_fence();
        wg_ss256(d, a, b, v != 0);
        wg_ss256(d, a + 2, b + 128, 1);
        wg_ss256(d, a + 4, b + 256, 1);
        wg_ss256(d, a + 6, b + 384, 1);
        wg_commit();
        if (v > 0) AC(1, t2 - t1);
        if (v == 3 && w == 0 && warp == 1 && (mc & 7) < 5 && lane < 2) tma_prefetch3(&tm_w2, f * 256 + lane * 128, (mc & 7) * 2 + rank);
        if (v == 8) {
          if (tid == 0 && w == 0) STAMP(4);
          if (!DBG(4)) mbar_wait(bars + 8 * B_BEXT, 0);
          const float2 sa = lds64f(sb + OFF_STAT + (w * 64 + warp * 16 + g) * 8), sc = lds64f(sb + OFF_STAT + (w * 64 + warp * 16 + g + 8) * 8);
          const float da = rcp_fast(sa.y), dc = rcp_fast(sc.y);
          const float mha = bf_round(sa.x), mhc = bf_round(sc.x), dha = bf_round(da), dhc = bf_round(dc);
          const float x0 = t4 == 0 ? mha : t4 == 1 ? sa.x - mha : da - dha, x1 = t4 == 0 ? mha : t4 == 1 ? dha : sa.x - mha;
          const float y0 = t4 == 0 ? mhc : t4 == 1 ? sc.x - mhc : dc - dhc, y1 = t4 == 0 ? mhc : t4 == 1 ? dhc : sc.x - mhc;
          e0 = t4 == 3 ? 0u : pack2(x0, x1); e1 = t4 == 3 ? 0u : pack2(y0, y1);
        }
        wg_wait<1>();
        TK(t3);
        if (v > 0) {
          release((v - 1) & 3);
          if (w == 1 && warp == 0) load_stage(v + 3);
        }
        TK(t5);
        AC(0, t5 - t3);
      }
      wg_fence();
      wg_rs256(d, e0, e1, 0u, 0u, (((sb + OFF_C) & 0x3FFFF) >> 4) | (128u << 16));
      wg_commit();
      wg_wait<0>();
      bar_arrive(6, 384);
      release(1);
      if (tid == 0) STAMP(13 + w);
      if (w == 1 && warp == 0) load_stage(13);
      if (w == 1) bar_sync(5, 256);
      const float k0 = 0.7978845608028654f, k1 = 0.7978845608028654f * 0.044715f;
      const float ra = lds64f(sb + OFF_STAT + (w * 64 + warp * 16 + g) * 8).y, rc = lds64f(sb + OFF_STAT + (w * 64 + warp * 16 + g + 8) * 8).y;
      const float h0 = 0.5f * ra, c10 = k0 * ra, c30 = k1 * ra * ra * ra;
      const float h1 = 0.5f * rc, c11 = k0 * rc, c31 = k1 * rc * rc * rc;
#pragma unroll
      for (int i = 0; i < 64; i++) {
        const float hh = (i & 1) ? h1 : h0, c1 = (i & 1) ? c11 : c10, c3 = (i & 1) ? c31 : c30;
        const float a = d[2 * i], b = d[2 * i + 1];
        const float ta = tanh_fast(a * fmaf(a * a, c3, c1)), tb = tanh_fast(b * fmaf(b * b, c3, c1));
        const float pa = a * hh, pb = b * hh;
        hf[i] = pack2(fmaf(pa, ta, pa), fmaf(pb, tb, pb));
      }
      if (w == 0) { sts32(bars + 8 * B_NUM, hf[63] ^ hf[60] ^ hf[57]); bar_arrive(5, 256); }
      if (tid == 0) STAMP(15 + w);
    }
    {
      float d[64];
      const uint32_t wlo = (((sb + OFF_W) & 0x3FFFF) >> 4) | (1024u << 16);
      const uint32_t sta = sb + OFF_X + w * 32768 + (warp * 16 + (lane & 15)) * 128;
      const int l7 = lane & 7;
#pragma unroll 1
      for (int qi = 0; qi < 5; qi++) {
        const int q = chunk_of(qi);
        const uint32_t hb = ((qi + 1) & 1) * 2, ph = ((qi + 5) >> 1) & 1;
        TK(u0);
        if (w == 1) bar_sync(7 + 2 * (qi & 1), 256); else if (qi >= 2) bar_sync(8, 256);
#pragma unroll
        for (int j = 0; j < 2; j++) {
          TK(u1);
          mbar_wait(bars + 8 * (B_WF + hb + j), ph);
          TK(u2);
          const uint32_t b = wlo + (hb + j) * 2048;
          wg_fence();
#pragma unroll
          for (int kk = 0; kk < 8; kk++) wg_rs128(d, &hf[32 * j + 4 * kk], b + 128 * kk, j + kk != 0);
          wg_commit();
          AC(3, u2 - u1); if (j == 0) AC(2, u1 - u0);
          if (j == 0 && w == 0 && warp == 0 && (qi == 2 || qi == 3)) load_stage(13 + 2 * qi);
        }
        if (w == 0) bar_arrive(7 + 2 * (qi & 1), 256); else if (qi >= 1 && qi < 4) bar_arrive(8, 256);
        wg_wait<1>();
        if (qi < 3) { release(hb); if (w == 1 && warp == 0) load_stage(14 + 2 * qi); }
        TK(v0);
        TK(v1);
        wg_wait<0>();
        TK(v2);
        AC(4, v1 - v0); AC(5, v2 - v1);
        if (qi < 3) release(hb + 1);
        if (qi == 0) { mbar_wait(we_l + 8, 0); if (!DBG(4)) mbar_wait(bars + 8 * B_INIT, 0); fence_async(); }
        const uint32_t st = sta + (qi & 1) * 16384;
        if (qi == 4 && f < 5) {
          if (!DBG(4)) mbar_wait(bars + 8 * B_Z, 0); else mbar_wait(bars + 8 * B_XT, 0);
#pragma unroll
          for (int cp = 0; cp < 8; cp++) {
            const uint32_t a = st + (cp >> 2) * 8192 + (((2 * (cp & 3) + (lane >> 4)) ^ l7) << 4);
            uint32_t z[4];
            ldsm4(a, z);
            stsm4(a, hadd2(pack2(d[8 * cp], d[8 * cp + 1]), z[0]), hadd2(pack2(d[8 * cp + 2], d[8 * cp + 3]), z[1]),
                     hadd2(pack2(d[8 * cp + 4], d[8 * cp + 5]), z[2]), hadd2(pack2(d[8 * cp + 6], d[8 * cp + 7]), z[3]));
          }
        } else {
#pragma unroll
          for (int cp = 0; cp < 8; cp++) {
            const uint32_t a = st + (cp >> 2) * 8192 + (((2 * (cp & 3) + (lane >> 4)) ^ l7) << 4);
            stsm4(a, pack2(d[8 * cp], d[8 * cp + 1]), pack2(d[8 * cp + 2], d[8 * cp + 3]), pack2(d[8 * cp + 4], d[8 * cp + 5]), pack2(d[8 * cp + 6], d[8 * cp + 7]));
          }
        }
        TK(v3);
        fence_async_smem();
        if (warp == 0) bulk_wait_read<0>();
        bar_sync(1 + wgi, 128);
        TK(v4);
        if (qi < 4) { AC(6, v3 - v2); AC(7, v4 - v3); }
        if (warp == 0 && elect()) {
          const uint32_t src = sb + OFF_X + w * 32768 + (qi & 1) * 16384;
          tma_red(&tm_out, q * 128, mt * 128 + w * 64, src);
          tma_red(&tm_out, q * 128 + 64, mt * 128 + w * 64, src + 8192);
          bulk_commit();
          if (qi == 3 && f < 5) {
            const uint32_t dst = sb + OFF_X + w * 32768;
            mbar_expect(bars + 8 * B_XT, 16384);
            tma_ld(dst, &tm_x64, f * 128, mt * 128 + w * 64, bars + 8 * B_XT);
            tma_ld(dst + 8192, &tm_x64, f * 128 + 64, mt * 128 + w * 64, bars + 8 * B_XT);
          }
          STAMP(17 + w * 5 + qi);
        }
        if (w == 1 && warp == 0 && qi == 0) load_stage(15);
      }
      if (warp == 0) bulk_wait_read<0>();
      if (tid == 0) STAMP(27 + w);
      DUMP();
    }
  }
}

typedef CUresult (*EncodeFn)(CUtensorMap*, CUtensorMapDataType, cuuint32_t, void*, const cuuint64_t*, const cuuint64_t*, const cuuint32_t*,
                             const cuuint32_t*, CUtensorMapInterleave, CUtensorMapSwizzle, CUtensorMapL2promotion, CUtensorMapFloatOOBfill);

CUtensorMap make_map(EncodeFn enc, const void* p, uint64_t d0, uint64_t d1, uint32_t b0, uint32_t b1) {
  CUtensorMap m;
  cuuint64_t gd[2] = {d0, d1}, gs[1] = {d0 * 2};
  cuuint32_t bx[2] = {b0, b1}, es[2] = {1, 1};
  enc(&m, CU_TENSOR_MAP_DATA_TYPE_BFLOAT16, 2, const_cast<void*>(p), gd, gs, bx, es, CU_TENSOR_MAP_INTERLEAVE_NONE,
      CU_TENSOR_MAP_SWIZZLE_128B, CU_TENSOR_MAP_L2_PROMOTION_L2_256B, CU_TENSOR_MAP_FLOAT_OOB_FILL_NONE);
  return m;
}

CUtensorMap make_map3(EncodeFn enc, const void* p, uint64_t cols, uint64_t rows, uint32_t brows, uint32_t bgroups) {
  CUtensorMap m;
  cuuint64_t gd[3] = {64, rows, cols / 64}, gs[2] = {cols * 2, 128};
  cuuint32_t bx[3] = {64, brows, bgroups}, es[3] = {1, 1, 1};
  enc(&m, CU_TENSOR_MAP_DATA_TYPE_BFLOAT16, 3, const_cast<void*>(p), gd, gs, bx, es, CU_TENSOR_MAP_INTERLEAVE_NONE,
      CU_TENSOR_MAP_SWIZZLE_128B, CU_TENSOR_MAP_L2_PROMOTION_L2_256B, CU_TENSOR_MAP_FLOAT_OOB_FILL_NONE);
  return m;
}

CUtensorMap make_map8(EncodeFn enc, const void* p) {
  CUtensorMap m;
  cuuint64_t gd[3] = {D_, S_ / 8, 8}, gs[2] = {8 * D_ * 2, D_ * 2};
  cuuint32_t bx[3] = {8, 128, 8}, es[3] = {1, 1, 1};
  enc(&m, CU_TENSOR_MAP_DATA_TYPE_BFLOAT16, 3, const_cast<void*>(p), gd, gs, bx, es, CU_TENSOR_MAP_INTERLEAVE_NONE,
      CU_TENSOR_MAP_SWIZZLE_NONE, SLAB_PROMO, CU_TENSOR_MAP_FLOAT_OOB_FILL_NONE);
  return m;
}

}

extern "C" void kernel_launch(void* const* d_in, const int* in_sizes, int n_in, void* d_out, int out_size) {
  (void)in_sizes; (void)n_in; (void)out_size;
  static EncodeFn enc = nullptr;
  static void* scr = nullptr;
  if (!enc) {
    void* fn = nullptr;
    cudaDriverEntryPointQueryResult q;
    cudaGetDriverEntryPoint("cuTensorMapEncodeTiled", &fn, cudaEnableDefault, &q);
    enc = (EncodeFn)fn;
    cudaGetSymbolAddress(&scr, g_scr);
    cudaFuncSetAttribute(fused_kernel, cudaFuncAttributeMaxDynamicSharedMemorySize, SMEM_BYTES);
  }
  Params P;
  P.x = (const __nv_bfloat16*)d_in[0]; P.k = (const __nv_bfloat16*)d_in[1]; P.v = (const __nv_bfloat16*)d_in[2];
  P.shift = (const __nv_bfloat16*)d_in[3]; P.h = (const __nv_bfloat16*)d_in[4]; P.dv = (const __nv_bfloat16*)d_in[5];
  P.w1 = (const __nv_bfloat16*)d_in[7]; P.b1 = (const __nv_bfloat16*)d_in[8]; P.b2 = (const __nv_bfloat16*)d_in[10];
  P.out = (__nv_bfloat16*)d_out;
  P.s = (Scratch*)scr;
  const CUtensorMap tm_x = make_map(enc, d_in[0], D_, S_, 64, 128), tm_x64 = make_map(enc, d_in[0], D_, S_, 64, 64);
  const CUtensorMap tm_w1 = make_map3(enc, d_in[7], F_, D_, 64, 2), tm_w2 = make_map3(enc, d_in[9], D_, F_, 128, 1);
  const CUtensorMap tm_out = make_map(enc, d_out, D_, S_, 64, 64), tm_yt = make_map(enc, P.s->yt, S_, D_, 64, 128);
  const CUtensorMap tm_k8 = make_map8(enc, d_in[1]), tm_v8 = make_map8(enc, d_in[2]);
  fused_kernel<<<NCTA, NTHR, SMEM_BYTES>>>(P, tm_x, tm_x64, tm_w1, tm_w2, tm_out, tm_yt, tm_k8, tm_v8);
}
```

```cpp
#include <cuda_runtime.h>
#include <cuda_bf16.h>
#include <cuda.h>
#include <stdint.h>

namespace {

constexpr int S_ = 2048, D_ = 640, F_ = 1536;
constexpr int NCTA = 132, NTHR = 384;
#define SLAB_PROMO CU_TENSOR_MAP_L2_PROMOTION_L2_128B
#define J3_GATE 0
#define CSTAG 400
#define W2PF 3
#define MPOLL 0
#define EXTV 8
#define XPROMO CU_TENSOR_MAP_L2_PROMOTION_L2_256B
#define FIRST_GATE 3
constexpr int CONV_CL0 = 4, CONV_NCL = 18;

constexpr int C_KV = 0, C_Y = 10, C_INIT = 15, C_EPOCH = 16, C_NUM = 17;
struct Scratch {
  unsigned cnt[64 * 32];
  float4 stats[S_];
  float4 cs[2 * 4 * 6 * 96];
  __nv_bfloat16 ur[D_ * S_];
  __nv_bfloat16 yt[D_ * S_];
};
__device__ __align__(1024) Scratch g_scr;
extern __shared__ __align__(1024) uint8_t smem_raw[];
#define SMB ((uint32_t)__cvta_generic_to_shared(smem_raw))

constexpr int OFF_X = 0;
constexpr int OFF_W = 65536;
constexpr int OFF_C = OFF_W + 8 * 16384;
constexpr int ST_U = 0, ST_H0 = 4480, ST_H1 = 4480 + 4224 + 64, ST_BYTES = 13056;
constexpr int CA_MLP = 16384 + 4096 + ST_BYTES;
constexpr int CV_X = 0, CV_Y = 49152, CV_ST = 65536, CV_LN = CV_ST + 6 * ST_BYTES, LN_BYTES = 25600, CV_UX = CV_LN + 3 * LN_BYTES;
constexpr int OFF_STAT = OFF_C + CA_MLP;
constexpr int OFF_BAR = OFF_STAT + 1024;
constexpr int SMEM_BYTES = OFF_BAR + 320 + 256;
enum { B_WF = 0, B_WE = 4, B_BEXT = 8, B_U = 9, B_Y = 15, B_XT = 16, B_INIT = 17, B_NUM = 18, B_KV = B_WF, B_LN = B_WF + 2 };
static_assert(CV_UX + 2 * ST_H0 <= OFF_STAT, "smem");

__device__ __forceinline__ uint32_t smem_u32(const void* p) { return (uint32_t)__cvta_generic_to_shared(p); }
__device__ __forceinline__ void mbar_init(uint32_t b, int c) { asm volatile("mbarrier.init.shared::cta.b64 [%0], %1;" :: "r"(b), "r"(c)); }
__device__ __forceinline__ void mbar_expect(uint32_t b, uint32_t bytes) { asm volatile("mbarrier.arrive.expect_tx.shared::cta.b64 _, [%0], %1;" :: "r"(b), "r"(bytes) : "memory"); }
__device__ __forceinline__ void mbar_arrive(uint32_t b) { asm volatile("mbarrier.arrive.shared::cta.b64 _, [%0];" :: "r"(b) : "memory"); }
__device__ __forceinline__ void mbar_arrive_cl(uint32_t b) { asm volatile("mbarrier.arrive.shared::cluster.b64 _, [%0];" :: "r"(b) : "memory"); }
__device__ __forceinline__ void mbar_wait(uint32_t b, uint32_t ph) {
  asm volatile("{\n.reg .pred p;\n.reg .u32 n;\nmov.u32 n, 0;\nWL:\nmbarrier.try_wait.parity.shared::cta.b64 p, [%0], %1;\n@p bra WD;\n"
               "add.u32 n, n, 1;\nsetp.lt.u32 p, n, 1000000;\n@p bra WL;\nWD:\n}\n" :: "r"(b), "r"(ph) : "memory");
}
__device__ __forceinline__ uint32_t mapa(uint32_t a, uint32_t r) { uint32_t o; asm("mapa.shared::cluster.u32 %0, %1, %2;" : "=r"(o) : "r"(a), "r"(r)); return o; }
__device__ __forceinline__ void flag_wait(const unsigned* cnt, int c, unsigned target) {
  asm volatile("{\n.reg .pred p;\n.reg .u32 n, v;\nmov.u32 n, 0;\nFL:\nld.relaxed.gpu.global.u32 v, [%0];\nsub.u32 v, v, %1;\nsetp.ge.s32 p, v, 0;\n@p bra FD;\n"
               "nanosleep.u32 20;\nadd.u32 n, n, 1;\nsetp.lt.u32 p, n, 2000000;\n@p bra FL;\nFD:\n}\n" :: "l"(cnt + c * 32), "r"(target) : "memory");
}
__device__ __forceinline__ bool elect() { uint32_t r; asm volatile("{.reg .pred p; elect.sync _|p, 0xffffffff; selp.u32 %0, 1, 0, p;}" : "=r"(r)); return r; }
__device__ __forceinline__ void flag_add(unsigned* cnt, int c) { asm volatile("red.release.gpu.global.add.u32 [%0], 1;" :: "l"(cnt + c * 32) : "memory"); }
__device__ __forceinline__ void fence_async() { asm volatile("fence.proxy.async.global;" ::: "memory"); }
__device__ __forceinline__ void fence_gpu() { asm volatile("fence.acq_rel.gpu;" ::: "memory"); }
__device__ __forceinline__ void flag_add_relaxed(unsigned* cnt, int c) { asm volatile("red.relaxed.gpu.global.add.u32 [%0], 1;" :: "l"(cnt + c * 32) : "memory"); }
__device__ __forceinline__ bool mbar_test(uint32_t b, uint32_t ph) {
  uint32_t ok; asm volatile("{.reg .pred p; mbarrier.test_wait.parity.shared::cta.b64 p, [%1], %2; selp.u32 %0, 1, 0, p;}" : "=r"(ok) : "r"(b), "r"(ph) : "memory"); return ok;
}
__device__ __forceinline__ void red4f(float* p, float a, float b, float c, float d) { asm volatile("red.relaxed.gpu.global.add.v4.f32 [%0], {%1,%2,%3,%4};" :: "l"(p), "f"(a), "f"(b), "f"(c), "f"(d) : "memory"); }
__device__ __forceinline__ void tma_prefetch3(const CUtensorMap* m, int y, int z) { asm volatile("cp.async.bulk.prefetch.tensor.3d.L2.global.tile [%0, {0, %1, %2}];" :: "l"(m), "r"(y), "r"(z) : "memory"); }
__device__ __forceinline__ void map_prefetch(const CUtensorMap* m) { asm volatile("prefetch.tensormap [%0];" :: "l"(m) : "memory"); }
__device__ __forceinline__ void fence_async_smem() { asm volatile("fence.proxy.async.shared::cta;" ::: "memory"); }
__device__ __forceinline__ void bar_sync(int id, int n) { asm volatile("bar.sync %0, %1;" :: "r"(id), "r"(n) : "memory"); }
__device__ __forceinline__ void bar_arrive(int id, int n) { asm volatile("bar.arrive %0, %1;" :: "r"(id), "r"(n) : "memory"); }
__device__ __forceinline__ void bulk_g2s(uint32_t dst, const void* src, uint32_t bytes, uint32_t bar) {
  asm volatile("cp.async.bulk.shared::cluster.global.mbarrier::complete_tx::bytes [%0], [%1], %2, [%3];" :: "r"(dst), "l"(src), "r"(bytes), "r"(bar) : "memory");
}
__device__ __forceinline__ void bulk_s2g(void* dst, uint32_t src, uint32_t bytes) {
  asm volatile("cp.async.bulk.global.shared::cta.bulk_group [%0], [%1], %2;" :: "l"(dst), "r"(src), "r"(bytes) : "memory");
}
__device__ __forceinline__ void tma_ld(uint32_t dst, const CUtensorMap* m, int x, int y, uint32_t bar) {
  asm volatile("cp.async.bulk.tensor.2d.shared::cluster.global.mbarrier::complete_tx::bytes [%0], [%1, {%3, %4}], [%2];"
               :: "r"(dst), "l"(m), "r"(bar), "r"(x), "r"(y) : "memory");
}
__device__ __forceinline__ void tma_ld3(uint32_t dst, const CUtensorMap* m, int y, int z, uint32_t bar) {
  asm volatile("cp.async.bulk.tensor.3d.shared::cluster.global.mbarrier::complete_tx::bytes [%0], [%1, {0, %3, %4}], [%2];"
               :: "r"(dst), "l"(m), "r"(bar), "r"(y), "r"(z) : "memory");
}
__device__ __forceinline__ void tma_ld3_mc(uint32_t dst, const CUtensorMap* m, int y, int z, uint32_t bar) {
  asm volatile("cp.async.bulk.tensor.3d.shared::cluster.global.mbarrier::complete_tx::bytes.multicast::cluster [%0], [%1, {0, %3, %4}], [%2], %5;"
               :: "r"(dst), "l"(m), "r"(bar), "r"(y), "r"(z), "h"((uint16_t)3) : "memory");
}
__device__ __forceinline__ void tma_ld3x(uint32_t dst, const CUtensorMap* m, int x, int y, uint32_t bar) {
  asm volatile("cp.async.bulk.tensor.3d.shared::cluster.global.mbarrier::complete_tx::bytes [%0], [%1, {%3, %4, 0}], [%2];"
               :: "r"(dst), "l"(m), "r"(bar), "r"(x), "r"(y) : "memory");
}
__device__ __forceinline__ void tma_st3(const CUtensorMap* m, int x, int y, uint32_t src) {
  asm volatile("cp.async.bulk.tensor.3d.global.shared::cta.tile.bulk_group [%0, {%2, %3, 0}], [%1];" :: "l"(m), "r"(src), "r"(x), "r"(y) : "memory");
}
__device__ __forceinline__ void tma_red(const CUtensorMap* m, int x, int y, uint32_t src) {
  asm volatile("cp.reduce.async.bulk.tensor.2d.global.shared::cta.add.tile.bulk_group [%0, {%2, %3}], [%1];" :: "l"(m), "r"(src), "r"(x), "r"(y) : "memory");
}
__device__ __forceinline__ void bulk_commit() { asm volatile("cp.async.bulk.commit_group;" ::: "memory"); }
template <int N> __device__ __forceinline__ void bulk_wait_read() { asm volatile("cp.async.bulk.wait_group.read %0;" :: "n"(N) : "memory"); }
template <int N> __device__ __forceinline__ void bulk_wait() { asm volatile("cp.async.bulk.wait_group %0;" :: "n"(N) : "memory"); }
__device__ __forceinline__ void wg_fence() { asm volatile("wgmma.fence.sync.aligned;" ::: "memory"); }
__device__ __forceinline__ void wg_commit() { asm volatile("wgmma.commit_group.sync.aligned;" ::: "memory"); }
template <int N> __device__ __forceinline__ void wg_wait() { asm volatile("wgmma.wait_group.sync.aligned %0;" :: "n"(N) : "memory"); }
__device__ __forceinline__ uint32_t lds32(uint32_t a) { uint32_t v; asm volatile("ld.shared.u32 %0, [%1];" : "=r"(v) : "r"(a)); return v; }
__device__ __forceinline__ void sts32(uint32_t a, uint32_t v) { asm volatile("st.shared.u32 [%0], %1;" :: "r"(a), "r"(v) : "memory"); }
__device__ __forceinline__ void sts32p(uint32_t a, uint32_t v, bool p) { asm volatile("{.reg .pred q; setp.ne.b32 q, %2, 0; @q st.shared.u32 [%0], %1;}" :: "r"(a), "r"(v), "r"((int)p) : "memory"); }
__device__ __forceinline__ void sts128(uint32_t a, uint32_t x, uint32_t y, uint32_t z, uint32_t w) { asm volatile("st.shared.v4.u32 [%0], {%1,%2,%3,%4};" :: "r"(a), "r"(x), "r"(y), "r"(z), "r"(w) : "memory"); }
__device__ __forceinline__ uint4 lds128(uint32_t a) { uint4 v; asm volatile("ld.shared.v4.u32 {%0,%1,%2,%3}, [%4];" : "=r"(v.x), "=r"(v.y), "=r"(v.z), "=r"(v.w) : "r"(a) : "memory"); return v; }
__device__ __forceinline__ uint2 lds64(uint32_t a) { uint2 v; asm volatile("ld.shared.v2.u32 {%0,%1}, [%2];" : "=r"(v.x), "=r"(v.y) : "r"(a) : "memory"); return v; }
__device__ __forceinline__ void st128(void* p, uint32_t x, uint32_t y, uint32_t z, uint32_t w) { asm volatile("st.v4.u32 [%0], {%1,%2,%3,%4};" :: "l"(p), "r"(x), "r"(y), "r"(z), "r"(w) : "memory"); }
__device__ __forceinline__ uint4 lds128_ro(uint32_t a) { uint4 v; asm("ld.shared.v4.u32 {%0,%1,%2,%3}, [%4];" : "=r"(v.x), "=r"(v.y), "=r"(v.z), "=r"(v.w) : "r"(a)); return v; }
__device__ __forceinline__ float2 lds64f(uint32_t a) { float2 v; asm volatile("ld.shared.v2.f32 {%0,%1}, [%2];" : "=f"(v.x), "=f"(v.y) : "r"(a) : "memory"); return v; }
__device__ __forceinline__ float4 lds128f(uint32_t a) { float4 v; asm volatile("ld.shared.v4.f32 {%0,%1,%2,%3}, [%4];" : "=f"(v.x), "=f"(v.y), "=f"(v.z), "=f"(v.w) : "r"(a)); return v; }
__device__ __forceinline__ void stsm4(uint32_t a, uint32_t x, uint32_t y, uint32_t z, uint32_t w) { asm volatile("stmatrix.sync.aligned.m8n8.x4.shared.b16 [%0], {%1,%2,%3,%4};" :: "r"(a), "r"(x), "r"(y), "r"(z), "r"(w) : "memory"); }
__device__ __forceinline__ void stsm4t(uint32_t a, uint32_t x, uint32_t y, uint32_t z, uint32_t w) { asm volatile("stmatrix.sync.aligned.m8n8.x4.trans.shared.b16 [%0], {%1,%2,%3,%4};" :: "r"(a), "r"(x), "r"(y), "r"(z), "r"(w) : "memory"); }
__device__ __forceinline__ void ldsm4(uint32_t a, uint32_t* r) { asm volatile("ldmatrix.sync.aligned.m8n8.x4.shared.b16 {%0,%1,%2,%3}, [%4];" : "=r"(r[0]), "=r"(r[1]), "=r"(r[2]), "=r"(r[3]) : "r"(a) : "memory"); }
__device__ __forceinline__ void ldsm4t(uint32_t a, uint32_t* r) { asm volatile("ldmatrix.sync.aligned.m8n8.x4.trans.shared.b16 {%0,%1,%2,%3}, [%4];" : "=r"(r[0]), "=r"(r[1]), "=r"(r[2]), "=r"(r[3]) : "r"(a) : "memory"); }
__device__ __forceinline__ uint32_t pack2(float lo, float hi) { uint32_t r; asm("cvt.rn.bf16x2.f32 %0, %1, %2;" : "=r"(r) : "f"(hi), "f"(lo)); return r; }
__device__ __forceinline__ float bf_lo(uint32_t v) { return __uint_as_float(v << 16); }
__device__ __forceinline__ float bf_hi(uint32_t v) { return __uint_as_float(v & 0xffff0000u); }
__device__ __forceinline__ float bf_round(float v) { return bf_lo(pack2(v, 0.f)); }
__device__ __forceinline__ uint32_t hadd2(uint32_t a, uint32_t b) { uint32_t r; asm("add.rn.bf16x2 %0, %1, %2;" : "=r"(r) : "r"(a), "r"(b)); return r; }
__device__ __forceinline__ uint32_t hsub2(uint32_t a, uint32_t b) { uint32_t r; asm("sub.rn.bf16x2 %0, %1, %2;" : "=r"(r) : "r"(a), "r"(b)); return r; }
__device__ __forceinline__ uint32_t hmul2(uint32_t a, uint32_t b) { uint32_t r; asm("mul.rn.bf16x2 %0, %1, %2;" : "=r"(r) : "r"(a), "r"(b)); return r; }
__device__ __forceinline__ uint32_t hfma2(uint32_t a, uint32_t b, uint32_t c) { uint32_t r; asm("fma.rn.bf16x2 %0, %1, %2, %3;" : "=r"(r) : "r"(a), "r"(b), "r"(c)); return r; }
__device__ __forceinline__ float tanh_fast(float x) { float r; asm("tanh.approx.f32 %0, %1;" : "=f"(r) : "f"(x)); return r; }
__device__ __forceinline__ float rcp_fast(float x) { float r; asm("rcp.approx.ftz.f32 %0, %1;" : "=f"(r) : "f"(x)); return r; }
__device__ __forceinline__ float rsqrt_fast(float x) { float r; asm("rsqrt.approx.ftz.f32 %0, %1;" : "=f"(r) : "f"(x)); return r; }
__device__ __forceinline__ uint4 ldg128(const void* p) { uint4 v; asm volatile("ld.global.nc.L1::no_allocate.v4.u32 {%0,%1,%2,%3}, [%4];" : "=r"(v.x), "=r"(v.y), "=r"(v.z), "=r"(v.w) : "l"(p)); return v; }
__device__ __forceinline__ uint2 ldg64(const void* p) { uint2 v; asm volatile("ld.global.nc.L1::no_allocate.v2.u32 {%0,%1}, [%2];" : "=r"(v.x), "=r"(v.y) : "l"(p)); return v; }
__device__ __forceinline__ uint32_t ldg32(const void* p) { uint32_t v; asm volatile("ld.global.nc.u32 %0, [%1];" : "=r"(v) : "l"(p)); return v; }
__device__ __forceinline__ float4 ldcg128f(const void* p) { float4 v; asm volatile("ld.global.cg.v4.f32 {%0,%1,%2,%3}, [%4];" : "=f"(v.x), "=f"(v.y), "=f"(v.z), "=f"(v.w) : "l"(p) : "memory"); return v; }
__device__ __forceinline__ float4 ld_relaxed4(const void* p) { float4 v; asm volatile("ld.relaxed.gpu.global.v4.f32 {%0,%1,%2,%3}, [%4];" : "=f"(v.x), "=f"(v.y), "=f"(v.z), "=f"(v.w) : "l"(p) : "memory"); return v; }
__device__ __forceinline__ float2 ldcg64f(const void* p) { float2 v; asm volatile("ld.global.cg.v2.f32 {%0,%1}, [%2];" : "=f"(v.x), "=f"(v.y) : "l"(p) : "memory"); return v; }
__device__ __forceinline__ void stg128(void* p, uint32_t x, uint32_t y, uint32_t z, uint32_t w) { asm volatile("st.global.v4.u32 [%0], {%1,%2,%3,%4};" :: "l"(p), "r"(x), "r"(y), "r"(z), "r"(w) : "memory"); }
__device__ __forceinline__ void cluster_arrive() { asm volatile("barrier.cluster.arrive.relaxed.aligned;" ::: "memory"); }
__device__ __forceinline__ void cluster_wait() { asm volatile("barrier.cluster.wait.acquire.aligned;" ::: "memory"); }

__device__ __forceinline__ void wg_ss256(float (&d)[128], uint32_t alo, uint32_t blo, uint32_t sc) {
  asm volatile("{\n.reg .pred p;\n.reg .b64 da, db;\nmov.b64 da, {%128, 0x40000040};\nmov.b64 db, {%129, 0x40000040};\nsetp.ne.b32 p, %130, 0;\n"
    "wgmma.mma_async.sync.aligned.m64n256k16.f32.bf16.bf16 {%0, %1, %2, %3, %4, %5, %6, %7, %8, %9, %10, %11, %12, %13, %14, %15, %16, %17, %18, %19, %20, %21, %22, %23, %24, %25, %26, %27, %28, %29, %30, %31, %32, %33, %34, %35, %36, %37, %38, %39, %40, %41, %42, %43, %44, %45, %46, %47, %48, %49, %50, %51, %52, %53, %54, %55, %56, %57, %58, %59, %60, %61, %62, %63, %64, %65, %66, %67, %68, %69, %70, %71, %72, %73, %74, %75, %76, %77, %78, %79, %80, %81, %82, %83, %84, %85, %86, %87, %88, %89, %90, %91, %92, %93, %94, %95, %96, %97, %98, %99, %100, %101, %102, %103, %104, %105, %106, %107, %108, %109, %110, %111, %112, %113, %114, %115, %116, %117, %118, %119, %120, %121, %122, %123, %124, %125, %126, %127}, da, db, p, 1, 1, 0, 1;\n}\n"
    : "+f"(d[0]), "+f"(d[1]), "+f"(d[2]), "+f"(d[3]), "+f"(d[4]), "+f"(d[5]), "+f"(d[6]), "+f"(d[7]), "+f"(d[8]), "+f"(d[9]), "+f"(d[10]), "+f"(d[11]), "+f"(d[12]), "+f"(d[13]), "+f"(d[14]), "+f"(d[15]), "+f"(d[16]), "+f"(d[17]), "+f"(d[18]), "+f"(d[19]), "+f"(d[20]), "+f"(d[21]), "+f"(d[22]), "+f"(d[23]), "+f"(d[24]), "+f"(d[25]), "+f"(d[26]), "+f"(d[27]), "+f"(d[28]), "+f"(d[29]), "+f"(d[30]), "+f"(d[31]), "+f"(d[32]), "+f"(d[33]), "+f"(d[34]), "+f"(d[35]), "+f"(d[36]), "+f"(d[37]), "+f"(d[38]), "+f"(d[39]), "+f"(d[40]), "+f"(d[41]), "+f"(d[42]), "+f"(d[43]), "+f"(d[44]), "+f"(d[45]), "+f"(d[46]), "+f"(d[47]), "+f"(d[48]), "+f"(d[49]), "+f"(d[50]), "+f"(d[51]), "+f"(d[52]), "+f"(d[53]), "+f"(d[54]), "+f"(d[55]), "+f"(d[56]), "+f"(d[57]), "+f"(d[58]), "+f"(d[59]), "+f"(d[60]), "+f"(d[61]), "+f"(d[62]), "+f"(d[63]), "+f"(d[64]), "+f"(d[65]), "+f"(d[66]), "+f"(d[67]), "+f"(d[68]), "+f"(d[69]), "+f"(d[70]), "+f"(d[71]), "+f"(d[72]), "+f"(d[73]), "+f"(d[74]), "+f"(d[75]), "+f"(d[76]), "+f"(d[77]), "+f"(d[78]), "+f"(d[79]), "+f"(d[80]), "+f"(d[81]), "+f"(d[82]), "+f"(d[83]), "+f"(d[84]), "+f"(d[85]), "+f"(d[86]), "+f"(d[87]), "+f"(d[88]), "+f"(d[89]), "+f"(d[90]), "+f"(d[91]), "+f"(d[92]), "+f"(d[93]), "+f"(d[94]), "+f"(d[95]), "+f"(d[96]), "+f"(d[97]), "+f"(d[98]), "+f"(d[99]), "+f"(d[100]), "+f"(d[101]), "+f"(d[102]), "+f"(d[103]), "+f"(d[104]), "+f"(d[105]), "+f"(d[106]), "+f"(d[107]), "+f"(d[108]), "+f"(d[109]), "+f"(d[110]), "+f"(d[111]), "+f"(d[112]), "+f"(d[113]), "+f"(d[114]), "+f"(d[115]), "+f"(d[116]), "+f"(d[117]), "+f"(d[118]), "+f"(d[119]), "+f"(d[120]), "+f"(d[121]), "+f"(d[122]), "+f"(d[123]), "+f"(d[124]), "+f"(d[125]), "+f"(d[126]), "+f"(d[127]) : "r"(alo), "r"(blo), "r"(sc));
}
__device__ __forceinline__ void wg_rs256(float (&d)[128], uint32_t a0, uint32_t a1, uint32_t a2, uint32_t a3, uint32_t blo, uint32_t sc) {
  asm volatile("{\n.reg .pred p;\n.reg .b64 db;\nmov.b64 db, {%132, 0x40000040};\nsetp.ne.b32 p, %133, 0;\n"
    "wgmma.mma_async.sync.aligned.m64n256k16.f32.bf16.bf16 {%0, %1, %2, %3, %4, %5, %6, %7, %8, %9, %10, %11, %12, %13, %14, %15, %16, %17, %18, %19, %20, %21, %22, %23, %24, %25, %26, %27, %28, %29, %30, %31, %32, %33, %34, %35, %36, %37, %38, %39, %40, %41, %42, %43, %44, %45, %46, %47, %48, %49, %50, %51, %52, %53, %54, %55, %56, %57, %58, %59, %60, %61, %62, %63, %64, %65, %66, %67, %68, %69, %70, %71, %72, %73, %74, %75, %76, %77, %78, %79, %80, %81, %82, %83, %84, %85, %86, %87, %88, %89, %90, %91, %92, %93, %94, %95, %96, %97, %98, %99, %100, %101, %102, %103, %104, %105, %106, %107, %108, %109, %110, %111, %112, %113, %114, %115, %116, %117, %118, %119, %120, %121, %122, %123, %124, %125, %126, %127}, {%128,%129,%130,%131}, db, p, 1, 1, 1;\n}\n"
    : "+f"(d[0]), "+f"(d[1]), "+f"(d[2]), "+f"(d[3]), "+f"(d[4]), "+f"(d[5]), "+f"(d[6]), "+f"(d[7]), "+f"(d[8]), "+f"(d[9]), "+f"(d[10]), "+f"(d[11]), "+f"(d[12]), "+f"(d[13]), "+f"(d[14]), "+f"(d[15]), "+f"(d[16]), "+f"(d[17]), "+f"(d[18]), "+f"(d[19]), "+f"(d[20]), "+f"(d[21]), "+f"(d[22]), "+f"(d[23]), "+f"(d[24]), "+f"(d[25]), "+f"(d[26]), "+f"(d[27]), "+f"(d[28]), "+f"(d[29]), "+f"(d[30]), "+f"(d[31]), "+f"(d[32]), "+f"(d[33]), "+f"(d[34]), "+f"(d[35]), "+f"(d[36]), "+f"(d[37]), "+f"(d[38]), "+f"(d[39]), "+f"(d[40]), "+f"(d[41]), "+f"(d[42]), "+f"(d[43]), "+f"(d[44]), "+f"(d[45]), "+f"(d[46]), "+f"(d[47]), "+f"(d[48]), "+f"(d[49]), "+f"(d[50]), "+f"(d[51]), "+f"(d[52]), "+f"(d[53]), "+f"(d[54]), "+f"(d[55]), "+f"(d[56]), "+f"(d[57]), "+f"(d[58]), "+f"(d[59]), "+f"(d[60]), "+f"(d[61]), "+f"(d[62]), "+f"(d[63]), "+f"(d[64]), "+f"(d[65]), "+f"(d[66]), "+f"(d[67]), "+f"(d[68]), "+f"(d[69]), "+f"(d[70]), "+f"(d[71]), "+f"(d[72]), "+f"(d[73]), "+f"(d[74]), "+f"(d[75]), "+f"(d[76]), "+f"(d[77]), "+f"(d[78]), "+f"(d[79]), "+f"(d[80]), "+f"(d[81]), "+f"(d[82]), "+f"(d[83]), "+f"(d[84]), "+f"(d[85]), "+f"(d[86]), "+f"(d[87]), "+f"(d[88]), "+f"(d[89]), "+f"(d[90]), "+f"(d[91]), "+f"(d[92]), "+f"(d[93]), "+f"(d[94]), "+f"(d[95]), "+f"(d[96]), "+f"(d[97]), "+f"(d[98]), "+f"(d[99]), "+f"(d[100]), "+f"(d[101]), "+f"(d[102]), "+f"(d[103]), "+f"(d[104]), "+f"(d[105]), "+f"(d[106]), "+f"(d[107]), "+f"(d[108]), "+f"(d[109]), "+f"(d[110]), "+f"(d[111]), "+f"(d[112]), "+f"(d[113]), "+f"(d[114]), "+f"(d[115]), "+f"(d[116]), "+f"(d[117]), "+f"(d[118]), "+f"(d[119]), "+f"(d[120]), "+f"(d[121]), "+f"(d[122]), "+f"(d[123]), "+f"(d[124]), "+f"(d[125]), "+f"(d[126]), "+f"(d[127]) : "r"(a0), "r"(a1), "r"(a2), "r"(a3), "r"(blo), "r"(sc));
}
__device__ __forceinline__ void wg_rs256x(float (&d)[128], uint32_t a0, uint32_t a1, uint32_t blo) {
  asm volatile("{\n.reg .b64 db;\nmov.b64 db, {%131, 0x40000000};\n"
    "wgmma.mma_async.sync.aligned.m64n256k16.f32.bf16.bf16 {%0, %1, %2, %3, %4, %5, %6, %7, %8, %9, %10, %11, %12, %13, %14, %15, %16, %17, %18, %19, %20, %21, %22, %23, %24, %25, %26, %27, %28, %29, %30, %31, %32, %33, %34, %35, %36, %37, %38, %39, %40, %41, %42, %43, %44, %45, %46, %47, %48, %49, %50, %51, %52, %53, %54, %55, %56, %57, %58, %59, %60, %61, %62, %63, %64, %65, %66, %67, %68, %69, %70, %71, %72, %73, %74, %75, %76, %77, %78, %79, %80, %81, %82, %83, %84, %85, %86, %87, %88, %89, %90, %91, %92, %93, %94, %95, %96, %97, %98, %99, %100, %101, %102, %103, %104, %105, %106, %107, %108, %109, %110, %111, %112, %113, %114, %115, %116, %117, %118, %119, %120, %121, %122, %123, %124, %125, %126, %127}, {%128,%129,%130,%130}, db, 1, 1, 1, 1;\n}\n"
    : "+f"(d[0]), "+f"(d[1]), "+f"(d[2]), "+f"(d[3]), "+f"(d[4]), "+f"(d[5]), "+f"(d[6]), "+f"(d[7]), "+f"(d[8]), "+f"(d[9]), "+f"(d[10]), "+f"(d[11]), "+f"(d[12]), "+f"(d[13]), "+f"(d[14]), "+f"(d[15]), "+f"(d[16]), "+f"(d[17]), "+f"(d[18]), "+f"(d[19]), "+f"(d[20]), "+f"(d[21]), "+f"(d[22]), "+f"(d[23]), "+f"(d[24]), "+f"(d[25]), "+f"(d[26]), "+f"(d[27]), "+f"(d[28]), "+f"(d[29]), "+f"(d[30]), "+f"(d[31]), "+f"(d[32]), "+f"(d[33]), "+f"(d[34]), "+f"(d[35]), "+f"(d[36]), "+f"(d[37]), "+f"(d[38]), "+f"(d[39]), "+f"(d[40]), "+f"(d[41]), "+f"(d[42]), "+f"(d[43]), "+f"(d[44]), "+f"(d[45]), "+f"(d[46]), "+f"(d[47]), "+f"(d[48]), "+f"(d[49]), "+f"(d[50]), "+f"(d[51]), "+f"(d[52]), "+f"(d[53]), "+f"(d[54]), "+f"(d[55]), "+f"(d[56]), "+f"(d[57]), "+f"(d[58]), "+f"(d[59]), "+f"(d[60]), "+f"(d[61]), "+f"(d[62]), "+f"(d[63]), "+f"(d[64]), "+f"(d[65]), "+f"(d[66]), "+f"(d[67]), "+f"(d[68]), "+f"(d[69]), "+f"(d[70]), "+f"(d[71]), "+f"(d[72]), "+f"(d[73]), "+f"(d[74]), "+f"(d[75]), "+f"(d[76]), "+f"(d[77]), "+f"(d[78]), "+f"(d[79]), "+f"(d[80]), "+f"(d[81]), "+f"(d[82]), "+f"(d[83]), "+f"(d[84]), "+f"(d[85]), "+f"(d[86]), "+f"(d[87]), "+f"(d[88]), "+f"(d[89]), "+f"(d[90]), "+f"(d[91]), "+f"(d[92]), "+f"(d[93]), "+f"(d[94]), "+f"(d[95]), "+f"(d[96]), "+f"(d[97]), "+f"(d[98]), "+f"(d[99]), "+f"(d[100]), "+f"(d[101]), "+f"(d[102]), "+f"(d[103]), "+f"(d[104]), "+f"(d[105]), "+f"(d[106]), "+f"(d[107]), "+f"(d[108]), "+f"(d[109]), "+f"(d[110]), "+f"(d[111]), "+f"(d[112]), "+f"(d[113]), "+f"(d[114]), "+f"(d[115]), "+f"(d[116]), "+f"(d[117]), "+f"(d[118]), "+f"(d[119]), "+f"(d[120]), "+f"(d[121]), "+f"(d[122]), "+f"(d[123]), "+f"(d[124]), "+f"(d[125]), "+f"(d[126]), "+f"(d[127]) : "r"(a0), "r"(a1), "r"(0u), "r"(blo));
}
__device__ __forceinline__ void wg_rs128(float (&d)[64], const uint32_t* a, uint32_t blo, uint32_t sc) {
  asm volatile("{\n.reg .pred p;\n.reg .b64 db;\nmov.b64 db, {%68, 0x40000040};\nsetp.ne.b32 p, %69, 0;\n"
    "wgmma.mma_async.sync.aligned.m64n128k16.f32.bf16.bf16 {%0, %1, %2, %3, %4, %5, %6, %7, %8, %9, %10, %11, %12, %13, %14, %15, %16, %17, %18, %19, %20, %21, %22, %23, %24, %25, %26, %27, %28, %29, %30, %31, %32, %33, %34, %35, %36, %37, %38, %39, %40, %41, %42, %43, %44, %45, %46, %47, %48, %49, %50, %51, %52, %53, %54, %55, %56, %57, %58, %59, %60, %61, %62, %63}, {%64,%65,%66,%67}, db, p, 1, 1, 1;\n}\n"
    : "+f"(d[0]), "+f"(d[1]), "+f"(d[2]), "+f"(d[3]), "+f"(d[4]), "+f"(d[5]), "+f"(d[6]), "+f"(d[7]), "+f"(d[8]), "+f"(d[9]), "+f"(d[10]), "+f"(d[11]), "+f"(d[12]), "+f"(d[13]), "+f"(d[14]), "+f"(d[15]), "+f"(d[16]), "+f"(d[17]), "+f"(d[18]), "+f"(d[19]), "+f"(d[20]), "+f"(d[21]), "+f"(d[22]), "+f"(d[23]), "+f"(d[24]), "+f"(d[25]), "+f"(d[26]), "+f"(d[27]), "+f"(d[28]), "+f"(d[29]), "+f"(d[30]), "+f"(d[31]), "+f"(d[32]), "+f"(d[33]), "+f"(d[34]), "+f"(d[35]), "+f"(d[36]), "+f"(d[37]), "+f"(d[38]), "+f"(d[39]), "+f"(d[40]), "+f"(d[41]), "+f"(d[42]), "+f"(d[43]), "+f"(d[44]), "+f"(d[45]), "+f"(d[46]), "+f"(d[47]), "+f"(d[48]), "+f"(d[49]), "+f"(d[50]), "+f"(d[51]), "+f"(d[52]), "+f"(d[53]), "+f"(d[54]), "+f"(d[55]), "+f"(d[56]), "+f"(d[57]), "+f"(d[58]), "+f"(d[59]), "+f"(d[60]), "+f"(d[61]), "+f"(d[62]), "+f"(d[63]) : "r"(a[0]), "r"(a[1]), "r"(a[2]), "r"(a[3]), "r"(blo), "r"(sc));
}
template<int OFF, int SC> __device__ __forceinline__ void wg_rs32(float (&d)[64], const uint32_t* a, uint32_t blo);
template<> __device__ __forceinline__ void wg_rs32<0,0>(float (&d)[64], const uint32_t* a, uint32_t blo) {
  asm volatile("{\n.reg .pred p;\n.reg .b64 db;\nmov.b64 db, {%20, 8};\nsetp.ne.b32 p, 0, 0;\n"
    "wgmma.mma_async.sync.aligned.m64n32k16.f32.bf16.bf16 {%0, %1, %2, %3, %4, %5, %6, %7, %8, %9, %10, %11, %12, %13, %14, %15}, {%16,%17,%18,%19}, db, p, 1, 1, 0;\n}\n"
    : "+f"(d[0]), "+f"(d[1]), "+f"(d[2]), "+f"(d[3]), "+f"(d[4]), "+f"(d[5]), "+f"(d[6]), "+f"(d[7]), "+f"(d[8]), "+f"(d[9]), "+f"(d[10]), "+f"(d[11]), "+f"(d[12]), "+f"(d[13]), "+f"(d[14]), "+f"(d[15]) : "r"(a[0]), "r"(a[1]), "r"(a[2]), "r"(a[3]), "r"(blo));
}
template<> __device__ __forceinline__ void wg_rs32<0,1>(float (&d)[64], const uint32_t* a, uint32_t blo) {
  asm volatile("{\n.reg .pred p;\n.reg .b64 db;\nmov.b64 db, {%20, 8};\nsetp.ne.b32 p, 1, 0;\n"
    "wgmma.mma_async.sync.aligned.m64n32k16.f32.bf16.bf16 {%0, %1, %2, %3, %4, %5, %6, %7, %8, %9, %10, %11, %12, %13, %14, %15}, {%16,%17,%18,%19}, db, p, 1, 1, 0;\n}\n"
    : "+f"(d[0]), "+f"(d[1]), "+f"(d[2]), "+f"(d[3]), "+f"(d[4]), "+f"(d[5]), "+f"(d[6]), "+f"(d[7]), "+f"(d[8]), "+f"(d[9]), "+f"(d[10]), "+f"(d[11]), "+f"(d[12]), "+f"(d[13]), "+f"(d[14]), "+f"(d[15]) : "r"(a[0]), "r"(a[1]), "r"(a[2]), "r"(a[3]), "r"(blo));
}
template<> __device__ __forceinline__ void wg_rs32<16,0>(float (&d)[64], const uint32_t* a, uint32_t blo) {
  asm volatile("{\n.reg .pred p;\n.reg .b64 db;\nmov.b64 db, {%20, 8};\nsetp.ne.b32 p, 0, 0;\n"
    "wgmma.mma_async.sync.aligned.m64n32k16.f32.bf16.bf16 {%0, %1, %2, %3, %4, %5, %6, %7, %8, %9, %10, %11, %12, %13, %14, %15}, {%16,%17,%18,%19}, db, p, 1, 1, 0;\n}\n"
    : "+f"(d[16]), "+f"(d[17]), "+f"(d[18]), "+f"(d[19]), "+f"(d[20]), "+f"(d[21]), "+f"(d[22]), "+f"(d[23]), "+f"(d[24]), "+f"(d[25]), "+f"(d[26]), "+f"(d[27]), "+f"(d[28]), "+f"(d[29]), "+f"(d[30]), "+f"(d[31]) : "r"(a[0]), "r"(a[1]), "r"(a[2]), "r"(a[3]), "r"(blo));
}
template<> __device__ __forceinline__ void wg_rs32<16,1>(float (&d)[64], const uint32_t* a, uint32_t blo) {
  asm volatile("{\n.reg .pred p;\n.reg .b64 db;\nmov.b64 db, {%20, 8};\nsetp.ne.b32 p, 1, 0;\n"
    "wgmma.mma_async.sync.aligned.m64n32k16.f32.bf16.bf16 {%0, %1, %2, %3, %4, %5, %6, %7, %8, %9, %10, %11, %12, %13, %14, %15}, {%16,%17,%18,%19}, db, p, 1, 1, 0;\n}\n"
    : "+f"(d[16]), "+f"(d[17]), "+f"(d[18]), "+f"(d[19]), "+f"(d[20]), "+f"(d[21]), "+f"(d[22]), "+f"(d[23]), "+f"(d[24]), "+f"(d[25]), "+f"(d[26]), "+f"(d[27]), "+f"(d[28]), "+f"(d[29]), "+f"(d[30]), "+f"(d[31]) : "r"(a[0]), "r"(a[1]), "r"(a[2]), "r"(a[3]), "r"(blo));
}
template<> __device__ __forceinline__ void wg_rs32<32,0>(float (&d)[64], const uint32_t* a, uint32_t blo) {
  asm volatile("{\n.reg .pred p;\n.reg .b64 db;\nmov.b64 db, {%20, 8};\nsetp.ne.b32 p, 0, 0;\n"
    "wgmma.mma_async.sync.aligned.m64n32k16.f32.bf16.bf16 {%0, %1, %2, %3, %4, %5, %6, %7, %8, %9, %10, %11, %12, %13, %14, %15}, {%16,%17,%18,%19}, db, p, 1, 1, 0;\n}\n"
    : "+f"(d[32]), "+f"(d[33]), "+f"(d[34]), "+f"(d[35]), "+f"(d[36]), "+f"(d[37]), "+f"(d[38]), "+f"(d[39]), "+f"(d[40]), "+f"(d[41]), "+f"(d[42]), "+f"(d[43]), "+f"(d[44]), "+f"(d[45]), "+f"(d[46]), "+f"(d[47]) : "r"(a[0]), "r"(a[1]), "r"(a[2]), "r"(a[3]), "r"(blo));
}
template<> __device__ __forceinline__ void wg_rs32<32,1>(float (&d)[64], const uint32_t* a, uint32_t blo) {
  asm volatile("{\n.reg .pred p;\n.reg .b64 db;\nmov.b64 db, {%20, 8};\nsetp.ne.b32 p, 1, 0;\n"
    "wgmma.mma_async.sync.aligned.m64n32k16.f32.bf16.bf16 {%0, %1, %2, %3, %4, %5, %6, %7, %8, %9, %10, %11, %12, %13, %14, %15}, {%16,%17,%18,%19}, db, p, 1, 1, 0;\n}\n"
    : "+f"(d[32]), "+f"(d[33]), "+f"(d[34]), "+f"(d[35]), "+f"(d[36]), "+f"(d[37]), "+f"(d[38]), "+f"(d[39]), "+f"(d[40]), "+f"(d[41]), "+f"(d[42]), "+f"(d[43]), "+f"(d[44]), "+f"(d[45]), "+f"(d[46]), "+f"(d[47]) : "r"(a[0]), "r"(a[1]), "r"(a[2]), "r"(a[3]), "r"(blo));
}
template<> __device__ __forceinline__ void wg_rs32<48,0>(float (&d)[64], const uint32_t* a, uint32_t blo) {
  asm volatile("{\n.reg .pred p;\n.reg .b64 db;\nmov.b64 db, {%20, 8};\nsetp.ne.b32 p, 0, 0;\n"
    "wgmma.mma_async.sync.aligned.m64n32k16.f32.bf16.bf16 {%0, %1, %2, %3, %4, %5, %6, %7, %8, %9, %10, %11, %12, %13, %14, %15}, {%16,%17,%18,%19}, db, p, 1, 1, 0;\n}\n"
    : "+f"(d[48]), "+f"(d[49]), "+f"(d[50]), "+f"(d[51]), "+f"(d[52]), "+f"(d[53]), "+f"(d[54]), "+f"(d[55]), "+f"(d[56]), "+f"(d[57]), "+f"(d[58]), "+f"(d[59]), "+f"(d[60]), "+f"(d[61]), "+f"(d[62]), "+f"(d[63]) : "r"(a[0]), "r"(a[1]), "r"(a[2]), "r"(a[3]), "r"(blo));
}
template<> __device__ __forceinline__ void wg_rs32<48,1>(float (&d)[64], const uint32_t* a, uint32_t blo) {
  asm volatile("{\n.reg .pred p;\n.reg .b64 db;\nmov.b64 db, {%20, 8};\nsetp.ne.b32 p, 1, 0;\n"
    "wgmma.mma_async.sync.aligned.m64n32k16.f32.bf16.bf16 {%0, %1, %2, %3, %4, %5, %6, %7, %8, %9, %10, %11, %12, %13, %14, %15}, {%16,%17,%18,%19}, db, p, 1, 1, 0;\n}\n"
    : "+f"(d[48]), "+f"(d[49]), "+f"(d[50]), "+f"(d[51]), "+f"(d[52]), "+f"(d[53]), "+f"(d[54]), "+f"(d[55]), "+f"(d[56]), "+f"(d[57]), "+f"(d[58]), "+f"(d[59]), "+f"(d[60]), "+f"(d[61]), "+f"(d[62]), "+f"(d[63]) : "r"(a[0]), "r"(a[1]), "r"(a[2]), "r"(a[3]), "r"(blo));
}
template<int OFF, int SC> __device__ __forceinline__ void wg_rs32f(float (&d)[128], const uint32_t* a, uint32_t blo);
template<> __device__ __forceinline__ void wg_rs32f<0,0>(float (&d)[128], const uint32_t* a, uint32_t blo) {
  asm volatile("{\n.reg .pred p;\n.reg .b64 db;\nmov.b64 db, {%20, 8};\nsetp.ne.b32 p, 0, 0;\n"
    "wgmma.mma_async.sync.aligned.m64n32k16.f32.bf16.bf16 {%0, %1, %2, %3, %4, %5, %6, %7, %8, %9, %10, %11, %12, %13, %14, %15}, {%16,%17,%18,%19}, db, p, 1, 1, 0;\n}\n"
    : "+f"(d[0]), "+f"(d[1]), "+f"(d[2]), "+f"(d[3]), "+f"(d[4]), "+f"(d[5]), "+f"(d[6]), "+f"(d[7]), "+f"(d[8]), "+f"(d[9]), "+f"(d[10]), "+f"(d[11]), "+f"(d[12]), "+f"(d[13]), "+f"(d[14]), "+f"(d[15]) : "r"(a[0]), "r"(a[1]), "r"(a[2]), "r"(a[3]), "r"(blo));
}
template<> __device__ __forceinline__ void wg_rs32f<0,1>(float (&d)[128], const uint32_t* a, uint32_t blo) {
  asm volatile("{\n.reg .pred p;\n.reg .b64 db;\nmov.b64 db, {%20, 8};\nsetp.ne.b32 p, 1, 0;\n"
    "wgmma.mma_async.sync.aligned.m64n32k16.f32.bf16.bf16 {%0, %1, %2, %3, %4, %5, %6, %7, %8, %9, %10, %11, %12, %13, %14, %15}, {%16,%17,%18,%19}, db, p, 1, 1, 0;\n}\n"
    : "+f"(d[0]), "+f"(d[1]), "+f"(d[2]), "+f"(d[3]), "+f"(d[4]), "+f"(d[5]), "+f"(d[6]), "+f"(d[7]), "+f"(d[8]), "+f"(d[9]), "+f"(d[10]), "+f"(d[11]), "+f"(d[12]), "+f"(d[13]), "+f"(d[14]), "+f"(d[15]) : "r"(a[0]), "r"(a[1]), "r"(a[2]), "r"(a[3]), "r"(blo));
}
template<> __device__ __forceinline__ void wg_rs32f<16,0>(float (&d)[128], const uint32_t* a, uint32_t blo) {
  asm volatile("{\n.reg .pred p;\n.reg .b64 db;\nmov.b64 db, {%20, 8};\nsetp.ne.b32 p, 0, 0;\n"
    "wgmma.mma_async.sync.aligned.m64n32k16.f32.bf16.bf16 {%0, %1, %2, %3, %4, %5, %6, %7, %8, %9, %10, %11, %12, %13, %14, %15}, {%16,%17,%18,%19}, db, p, 1, 1, 0;\n}\n"
    : "+f"(d[16]), "+f"(d[17]), "+f"(d[18]), "+f"(d[19]), "+f"(d[20]), "+f"(d[21]), "+f"(d[22]), "+f"(d[23]), "+f"(d[24]), "+f"(d[25]), "+f"(d[26]), "+f"(d[27]), "+f"(d[28]), "+f"(d[29]), "+f"(d[30]), "+f"(d[31]) : "r"(a[0]), "r"(a[1]), "r"(a[2]), "r"(a[3]), "r"(blo));
}
template<> __device__ __forceinline__ void wg_rs32f<16,1>(float (&d)[128], const uint32_t* a, uint32_t blo) {
  asm volatile("{\n.reg .pred p;\n.reg .b64 db;\nmov.b64 db, {%20, 8};\nsetp.ne.b32 p, 1, 0;\n"
    "wgmma.mma_async.sync.aligned.m64n32k16.f32.bf16.bf16 {%0, %1, %2, %3, %4, %5, %6, %7, %8, %9, %10, %11, %12, %13, %14, %15}, {%16,%17,%18,%19}, db, p, 1, 1, 0;\n}\n"
    : "+f"(d[16]), "+f"(d[17]), "+f"(d[18]), "+f"(d[19]), "+f"(d[20]), "+f"(d[21]), "+f"(d[22]), "+f"(d[23]), "+f"(d[24]), "+f"(d[25]), "+f"(d[26]), "+f"(d[27]), "+f"(d[28]), "+f"(d[29]), "+f"(d[30]), "+f"(d[31]) : "r"(a[0]), "r"(a[1]), "r"(a[2]), "r"(a[3]), "r"(blo));
}
template<> __device__ __forceinline__ void wg_rs32f<32,0>(float (&d)[128], const uint32_t* a, uint32_t blo) {
  asm volatile("{\n.reg .pred p;\n.reg .b64 db;\nmov.b64 db, {%20, 8};\nsetp.ne.b32 p, 0, 0;\n"
    "wgmma.mma_async.sync.aligned.m64n32k16.f32.bf16.bf16 {%0, %1, %2, %3, %4, %5, %6, %7, %8, %9, %10, %11, %12, %13, %14, %15}, {%16,%17,%18,%19}, db, p, 1, 1, 0;\n}\n"
    : "+f"(d[32]), "+f"(d[33]), "+f"(d[34]), "+f"(d[35]), "+f"(d[36]), "+f"(d[37]), "+f"(d[38]), "+f"(d[39]), "+f"(d[40]), "+f"(d[41]), "+f"(d[42]), "+f"(d[43]), "+f"(d[44]), "+f"(d[45]), "+f"(d[46]), "+f"(d[47]) : "r"(a[0]), "r"(a[1]), "r"(a[2]), "r"(a[3]), "r"(blo));
}
template<> __device__ __forceinline__ void wg_rs32f<32,1>(float (&d)[128], const uint32_t* a, uint32_t blo) {
  asm volatile("{\n.reg .pred p;\n.reg .b64 db;\nmov.b64 db, {%20, 8};\nsetp.ne.b32 p, 1, 0;\n"
    "wgmma.mma_async.sync.aligned.m64n32k16.f32.bf16.bf16 {%0, %1, %2, %3, %4, %5, %6, %7, %8, %9, %10, %11, %12, %13, %14, %15}, {%16,%17,%18,%19}, db, p, 1, 1, 0;\n}\n"
    : "+f"(d[32]), "+f"(d[33]), "+f"(d[34]), "+f"(d[35]), "+f"(d[36]), "+f"(d[37]), "+f"(d[38]), "+f"(d[39]), "+f"(d[40]), "+f"(d[41]), "+f"(d[42]), "+f"(d[43]), "+f"(d[44]), "+f"(d[45]), "+f"(d[46]), "+f"(d[47]) : "r"(a[0]), "r"(a[1]), "r"(a[2]), "r"(a[3]), "r"(blo));
}
template<> __device__ __forceinline__ void wg_rs32f<48,0>(float (&d)[128], const uint32_t* a, uint32_t blo) {
  asm volatile("{\n.reg .pred p;\n.reg .b64 db;\nmov.b64 db, {%20, 8};\nsetp.ne.b32 p, 0, 0;\n"
    "wgmma.mma_async.sync.aligned.m64n32k16.f32.bf16.bf16 {%0, %1, %2, %3, %4, %5, %6, %7, %8, %9, %10, %11, %12, %13, %14, %15}, {%16,%17,%18,%19}, db, p, 1, 1, 0;\n}\n"
    : "+f"(d[48]), "+f"(d[49]), "+f"(d[50]), "+f"(d[51]), "+f"(d[52]), "+f"(d[53]), "+f"(d[54]), "+f"(d[55]), "+f"(d[56]), "+f"(d[57]), "+f"(d[58]), "+f"(d[59]), "+f"(d[60]), "+f"(d[61]), "+f"(d[62]), "+f"(d[63]) : "r"(a[0]), "r"(a[1]), "r"(a[2]), "r"(a[3]), "r"(blo));
}
template<> __device__ __forceinline__ void wg_rs32f<48,1>(float (&d)[128], const uint32_t* a, uint32_t blo) {
  asm volatile("{\n.reg .pred p;\n.reg .b64 db;\nmov.b64 db, {%20, 8};\nsetp.ne.b32 p, 1, 0;\n"
    "wgmma.mma_async.sync.aligned.m64n32k16.f32.bf16.bf16 {%0, %1, %2, %3, %4, %5, %6, %7, %8, %9, %10, %11, %12, %13, %14, %15}, {%16,%17,%18,%19}, db, p, 1, 1, 0;\n}\n"
    : "+f"(d[48]), "+f"(d[49]), "+f"(d[50]), "+f"(d[51]), "+f"(d[52]), "+f"(d[53]), "+f"(d[54]), "+f"(d[55]), "+f"(d[56]), "+f"(d[57]), "+f"(d[58]), "+f"(d[59]), "+f"(d[60]), "+f"(d[61]), "+f"(d[62]), "+f"(d[63]) : "r"(a[0]), "r"(a[1]), "r"(a[2]), "r"(a[3]), "r"(blo));
}
template<> __device__ __forceinline__ void wg_rs32f<64,0>(float (&d)[128], const uint32_t* a, uint32_t blo) {
  asm volatile("{\n.reg .pred p;\n.reg .b64 db;\nmov.b64 db, {%20, 8};\nsetp.ne.b32 p, 0, 0;\n"
    "wgmma.mma_async.sync.aligned.m64n32k16.f32.bf16.bf16 {%0, %1, %2, %3, %4, %5, %6, %7, %8, %9, %10, %11, %12, %13, %14, %15}, {%16,%17,%18,%19}, db, p, 1, 1, 0;\n}\n"
    : "+f"(d[64]), "+f"(d[65]), "+f"(d[66]), "+f"(d[67]), "+f"(d[68]), "+f"(d[69]), "+f"(d[70]), "+f"(d[71]), "+f"(d[72]), "+f"(d[73]), "+f"(d[74]), "+f"(d[75]), "+f"(d[76]), "+f"(d[77]), "+f"(d[78]), "+f"(d[79]) : "r"(a[0]), "r"(a[1]), "r"(a[2]), "r"(a[3]), "r"(blo));
}
template<> __device__ __forceinline__ void wg_rs32f<64,1>(float (&d)[128], const uint32_t* a, uint32_t blo) {
  asm volatile("{\n.reg .pred p;\n.reg .b64 db;\nmov.b64 db, {%20, 8};\nsetp.ne.b32 p, 1, 0;\n"
    "wgmma.mma_async.sync.aligned.m64n32k16.f32.bf16.bf16 {%0, %1, %2, %3, %4, %5, %6, %7, %8, %9, %10, %11, %12, %13, %14, %15}, {%16,%17,%18,%19}, db, p, 1, 1, 0;\n}\n"
    : "+f"(d[64]), "+f"(d[65]), "+f"(d[66]), "+f"(d[67]), "+f"(d[68]), "+f"(d[69]), "+f"(d[70]), "+f"(d[71]), "+f"(d[72]), "+f"(d[73]), "+f"(d[74]), "+f"(d[75]), "+f"(d[76]), "+f"(d[77]), "+f"(d[78]), "+f"(d[79]) : "r"(a[0]), "r"(a[1]), "r"(a[2]), "r"(a[3]), "r"(blo));
}
template<> __device__ __forceinline__ void wg_rs32f<80,0>(float (&d)[128], const uint32_t* a, uint32_t blo) {
  asm volatile("{\n.reg .pred p;\n.reg .b64 db;\nmov.b64 db, {%20, 8};\nsetp.ne.b32 p, 0, 0;\n"
    "wgmma.mma_async.sync.aligned.m64n32k16.f32.bf16.bf16 {%0, %1, %2, %3, %4, %5, %6, %7, %8, %9, %10, %11, %12, %13, %14, %15}, {%16,%17,%18,%19}, db, p, 1, 1, 0;\n}\n"
    : "+f"(d[80]), "+f"(d[81]), "+f"(d[82]), "+f"(d[83]), "+f"(d[84]), "+f"(d[85]), "+f"(d[86]), "+f"(d[87]), "+f"(d[88]), "+f"(d[89]), "+f"(d[90]), "+f"(d[91]), "+f"(d[92]), "+f"(d[93]), "+f"(d[94]), "+f"(d[95]) : "r"(a[0]), "r"(a[1]), "r"(a[2]), "r"(a[3]), "r"(blo));
}
template<> __device__ __forceinline__ void wg_rs32f<80,1>(float (&d)[128], const uint32_t* a, uint32_t blo) {
  asm volatile("{\n.reg .pred p;\n.reg .b64 db;\nmov.b64 db, {%20, 8};\nsetp.ne.b32 p, 1, 0;\n"
    "wgmma.mma_async.sync.aligned.m64n32k16.f32.bf16.bf16 {%0, %1, %2, %3, %4, %5, %6, %7, %8, %9, %10, %11, %12, %13, %14, %15}, {%16,%17,%18,%19}, db, p, 1, 1, 0;\n}\n"
    : "+f"(d[80]), "+f"(d[81]), "+f"(d[82]), "+f"(d[83]), "+f"(d[84]), "+f"(d[85]), "+f"(d[86]), "+f"(d[87]), "+f"(d[88]), "+f"(d[89]), "+f"(d[90]), "+f"(d[91]), "+f"(d[92]), "+f"(d[93]), "+f"(d[94]), "+f"(d[95]) : "r"(a[0]), "r"(a[1]), "r"(a[2]), "r"(a[3]), "r"(blo));
}
template<> __device__ __forceinline__ void wg_rs32f<96,0>(float (&d)[128], const uint32_t* a, uint32_t blo) {
  asm volatile("{\n.reg .pred p;\n.reg .b64 db;\nmov.b64 db, {%20, 8};\nsetp.ne.b32 p, 0, 0;\n"
    "wgmma.mma_async.sync.aligned.m64n32k16.f32.bf16.bf16 {%0, %1, %2, %3, %4, %5, %6, %7, %8, %9, %10, %11, %12, %13, %14, %15}, {%16,%17,%18,%19}, db, p, 1, 1, 0;\n}\n"
    : "+f"(d[96]), "+f"(d[97]), "+f"(d[98]), "+f"(d[99]), "+f"(d[100]), "+f"(d[101]), "+f"(d[102]), "+f"(d[103]), "+f"(d[104]), "+f"(d[105]), "+f"(d[106]), "+f"(d[107]), "+f"(d[108]), "+f"(d[109]), "+f"(d[110]), "+f"(d[111]) : "r"(a[0]), "r"(a[1]), "r"(a[2]), "r"(a[3]), "r"(blo));
}
template<> __device__ __forceinline__ void wg_rs32f<96,1>(float (&d)[128], const uint32_t* a, uint32_t blo) {
  asm volatile("{\n.reg .pred p;\n.reg .b64 db;\nmov.b64 db, {%20, 8};\nsetp.ne.b32 p, 1, 0;\n"
    "wgmma.mma_async.sync.aligned.m64n32k16.f32.bf16.bf16 {%0, %1, %2, %3, %4, %5, %6, %7, %8, %9, %10, %11, %12, %13, %14, %15}, {%16,%17,%18,%19}, db, p, 1, 1, 0;\n}\n"
    : "+f"(d[96]), "+f"(d[97]), "+f"(d[98]), "+f"(d[99]), "+f"(d[100]), "+f"(d[101]), "+f"(d[102]), "+f"(d[103]), "+f"(d[104]), "+f"(d[105]), "+f"(d[106]), "+f"(d[107]), "+f"(d[108]), "+f"(d[109]), "+f"(d[110]), "+f"(d[111]) : "r"(a[0]), "r"(a[1]), "r"(a[2]), "r"(a[3]), "r"(blo));
}
template<> __device__ __forceinline__ void wg_rs32f<112,0>(float (&d)[128], const uint32_t* a, uint32_t blo) {
  asm volatile("{\n.reg .pred p;\n.reg .b64 db;\nmov.b64 db, {%20, 8};\nsetp.ne.b32 p, 0, 0;\n"
    "wgmma.mma_async.sync.aligned.m64n32k16.f32.bf16.bf16 {%0, %1, %2, %3, %4, %5, %6, %7, %8, %9, %10, %11, %12, %13, %14, %15}, {%16,%17,%18,%19}, db, p, 1, 1, 0;\n}\n"
    : "+f"(d[112]), "+f"(d[113]), "+f"(d[114]), "+f"(d[115]), "+f"(d[116]), "+f"(d[117]), "+f"(d[118]), "+f"(d[119]), "+f"(d[120]), "+f"(d[121]), "+f"(d[122]), "+f"(d[123]), "+f"(d[124]), "+f"(d[125]), "+f"(d[126]), "+f"(d[127]) : "r"(a[0]), "r"(a[1]), "r"(a[2]), "r"(a[3]), "r"(blo));
}
template<> __device__ __forceinline__ void wg_rs32f<112,1>(float (&d)[128], const uint32_t* a, uint32_t blo) {
  asm volatile("{\n.reg .pred p;\n.reg .b64 db;\nmov.b64 db, {%20, 8};\nsetp.ne.b32 p, 1, 0;\n"
    "wgmma.mma_async.sync.aligned.m64n32k16.f32.bf16.bf16 {%0, %1, %2, %3, %4, %5, %6, %7, %8, %9, %10, %11, %12, %13, %14, %15}, {%16,%17,%18,%19}, db, p, 1, 1, 0;\n}\n"
    : "+f"(d[112]), "+f"(d[113]), "+f"(d[114]), "+f"(d[115]), "+f"(d[116]), "+f"(d[117]), "+f"(d[118]), "+f"(d[119]), "+f"(d[120]), "+f"(d[121]), "+f"(d[122]), "+f"(d[123]), "+f"(d[124]), "+f"(d[125]), "+f"(d[126]), "+f"(d[127]) : "r"(a[0]), "r"(a[1]), "r"(a[2]), "r"(a[3]), "r"(blo));
}
template<int OFF, int SC> __device__ __forceinline__ void wg_rs64(float (&d)[64], const uint32_t* a, uint32_t blo);
template<> __device__ __forceinline__ void wg_rs64<0,0>(float (&d)[64], const uint32_t* a, uint32_t blo) {
  asm volatile("{\n.reg .pred p;\n.reg .b64 db;\nmov.b64 db, {%36, 8};\nsetp.ne.b32 p, 0, 0;\n"
    "wgmma.mma_async.sync.aligned.m64n64k16.f32.bf16.bf16 {%0, %1, %2, %3, %4, %5, %6, %7, %8, %9, %10, %11, %12, %13, %14, %15, %16, %17, %18, %19, %20, %21, %22, %23, %24, %25, %26, %27, %28, %29, %30, %31}, {%32,%33,%34,%35}, db, p, 1, 1, 0;\n}\n"
    : "+f"(d[0]), "+f"(d[1]), "+f"(d[2]), "+f"(d[3]), "+f"(d[4]), "+f"(d[5]), "+f"(d[6]), "+f"(d[7]), "+f"(d[8]), "+f"(d[9]), "+f"(d[10]), "+f"(d[11]), "+f"(d[12]), "+f"(d[13]), "+f"(d[14]), "+f"(d[15]), "+f"(d[16]), "+f"(d[17]), "+f"(d[18]), "+f"(d[19]), "+f"(d[20]), "+f"(d[21]), "+f"(d[22]), "+f"(d[23]), "+f"(d[24]), "+f"(d[25]), "+f"(d[26]), "+f"(d[27]), "+f"(d[28]), "+f"(d[29]), "+f"(d[30]), "+f"(d[31]) : "r"(a[0]), "r"(a[1]), "r"(a[2]), "r"(a[3]), "r"(blo));
}
template<> __device__ __forceinline__ void wg_rs64<0,1>(float (&d)[64], const uint32_t* a, uint32_t blo) {
  asm volatile("{\n.reg .pred p;\n.reg .b64 db;\nmov.b64 db, {%36, 8};\nsetp.ne.b32 p, 1, 0;\n"
    "wgmma.mma_async.sync.aligned.m64n64k16.f32.bf16.bf16 {%0, %1, %2, %3, %4, %5, %6, %7, %8, %9, %10, %11, %12, %13, %14, %15, %16, %17, %18, %19, %20, %21, %22, %23, %24, %25, %26, %27, %28, %29, %30, %31}, {%32,%33,%34,%35}, db, p, 1, 1, 0;\n}\n"
    : "+f"(d[0]), "+f"(d[1]), "+f"(d[2]), "+f"(d[3]), "+f"(d[4]), "+f"(d[5]), "+f"(d[6]), "+f"(d[7]), "+f"(d[8]), "+f"(d[9]), "+f"(d[10]), "+f"(d[11]), "+f"(d[12]), "+f"(d[13]), "+f"(d[14]), "+f"(d[15]), "+f"(d[16]), "+f"(d[17]), "+f"(d[18]), "+f"(d[19]), "+f"(d[20]), "+f"(d[21]), "+f"(d[22]), "+f"(d[23]), "+f"(d[24]), "+f"(d[25]), "+f"(d[26]), "+f"(d[27]), "+f"(d[28]), "+f"(d[29]), "+f"(d[30]), "+f"(d[31]) : "r"(a[0]), "r"(a[1]), "r"(a[2]), "r"(a[3]), "r"(blo));
}
template<> __device__ __forceinline__ void wg_rs64<32,0>(float (&d)[64], const uint32_t* a, uint32_t blo) {
  asm volatile("{\n.reg .pred p;\n.reg .b64 db;\nmov.b64 db, {%36, 8};\nsetp.ne.b32 p, 0, 0;\n"
    "wgmma.mma_async.sync.aligned.m64n64k16.f32.bf16.bf16 {%0, %1, %2, %3, %4, %5, %6, %7, %8, %9, %10, %11, %12, %13, %14, %15, %16, %17, %18, %19, %20, %21, %22, %23, %24, %25, %26, %27, %28, %29, %30, %31}, {%32,%33,%34,%35}, db, p, 1, 1, 0;\n}\n"
    : "+f"(d[32]), "+f"(d[33]), "+f"(d[34]), "+f"(d[35]), "+f"(d[36]), "+f"(d[37]), "+f"(d[38]), "+f"(d[39]), "+f"(d[40]), "+f"(d[41]), "+f"(d[42]), "+f"(d[43]), "+f"(d[44]), "+f"(d[45]), "+f"(d[46]), "+f"(d[47]), "+f"(d[48]), "+f"(d[49]), "+f"(d[50]), "+f"(d[51]), "+f"(d[52]), "+f"(d[53]), "+f"(d[54]), "+f"(d[55]), "+f"(d[56]), "+f"(d[57]), "+f"(d[58]), "+f"(d[59]), "+f"(d[60]), "+f"(d[61]), "+f"(d[62]), "+f"(d[63]) : "r"(a[0]), "r"(a[1]), "r"(a[2]), "r"(a[3]), "r"(blo));
}
template<> __device__ __forceinline__ void wg_rs64<32,1>(float (&d)[64], const uint32_t* a, uint32_t blo) {
  asm volatile("{\n.reg .pred p;\n.reg .b64 db;\nmov.b64 db, {%36, 8};\nsetp.ne.b32 p, 1, 0;\n"
    "wgmma.mma_async.sync.aligned.m64n64k16.f32.bf16.bf16 {%0, %1, %2, %3, %4, %5, %6, %7, %8, %9, %10, %11, %12, %13, %14, %15, %16, %17, %18, %19, %20, %21, %22, %23, %24, %25, %26, %27, %28, %29, %30, %31}, {%32,%33,%34,%35}, db, p, 1, 1, 0;\n}\n"
    : "+f"(d[32]), "+f"(d[33]), "+f"(d[34]), "+f"(d[35]), "+f"(d[36]), "+f"(d[37]), "+f"(d[38]), "+f"(d[39]), "+f"(d[40]), "+f"(d[41]), "+f"(d[42]), "+f"(d[43]), "+f"(d[44]), "+f"(d[45]), "+f"(d[46]), "+f"(d[47]), "+f"(d[48]), "+f"(d[49]), "+f"(d[50]), "+f"(d[51]), "+f"(d[52]), "+f"(d[53]), "+f"(d[54]), "+f"(d[55]), "+f"(d[56]), "+f"(d[57]), "+f"(d[58]), "+f"(d[59]), "+f"(d[60]), "+f"(d[61]), "+f"(d[62]), "+f"(d[63]) : "r"(a[0]), "r"(a[1]), "r"(a[2]), "r"(a[3]), "r"(blo));
}

struct Params {
  const __nv_bfloat16 *k, *v, *h;
  Scratch* s;
  const __nv_bfloat16 *shift, *dv, *x, *w1, *b1, *b2;
  __nv_bfloat16* out;
};

__device__ __forceinline__ void mma16816(float (&c)[4], uint32_t a0, uint32_t a1, uint32_t a2, uint32_t a3, uint32_t b0, uint32_t b1) {
  asm("mma.sync.aligned.m16n8k16.row.col.f32.bf16.bf16.f32 {%0,%1,%2,%3}, {%4,%5,%6,%7}, {%8,%9}, {%0,%1,%2,%3};"
               : "+f"(c[0]), "+f"(c[1]), "+f"(c[2]), "+f"(c[3]) : "r"(a0), "r"(a1), "r"(a2), "r"(a3), "r"(b0), "r"(b1));
}
__device__ __forceinline__ void ln_rows(uint32_t src, float4* stat, int nrows, unsigned ep, int lane) {
  const int g = lane >> 2, t4 = lane & 3;
  uint32_t a = src + g * 1280 + t4 * 16 + (g & 1) * 64, b = a ^ 64;
  asm volatile("" : "+r"(a), "+r"(b) :: "memory");
  const uint32_t one = 0x3F803F80u;
  float s0[4] = {0.f, 0.f, 0.f, 0.f}, s1[4] = {0.f, 0.f, 0.f, 0.f};
#pragma unroll
  for (int j = 0; j < 20; j++) {
    const uint4 u = lds128_ro(((j & 1) ? b : a) + (j >> 1) * 128), v = lds128_ro(((j & 1) ? b : a) + 8 * 1280 + (j >> 1) * 128);
    mma16816(s0, u.x, v.x, u.y, v.y, one, one);
    mma16816(s1, u.z, v.z, u.w, v.w, one, one);
  }
  const float m0 = (s0[0] + s1[0]) * (1.f / D_), m1 = (s0[2] + s1[2]) * (1.f / D_);
  const uint32_t p0 = pack2(m0, m0), p1 = pack2(m1, m1);
  float q0[4] = {0.f, 0.f, 0.f, 0.f}, q1[4] = {0.f, 0.f, 0.f, 0.f}, q2[4] = {0.f, 0.f, 0.f, 0.f}, q3[4] = {0.f, 0.f, 0.f, 0.f};
  s0[0] = s0[1] = s0[2] = s0[3] = s1[0] = s1[1] = s1[2] = s1[3] = 0.f;
  asm volatile("" : "+r"(a), "+r"(b) :: "memory");
#pragma unroll 4
  for (int j = 0; j < 20; j++) {
    uint4 u = lds128_ro(((j & 1) ? b : a) + (j >> 1) * 128), v = lds128_ro(((j & 1) ? b : a) + 8 * 1280 + (j >> 1) * 128);
    u.x = hsub2(u.x, p0); u.y = hsub2(u.y, p0); u.z = hsub2(u.z, p0); u.w = hsub2(u.w, p0);
    v.x = hsub2(v.x, p1); v.y = hsub2(v.y, p1); v.z = hsub2(v.z, p1); v.w = hsub2(v.w, p1);
    mma16816(q0, u.x, v.x, u.y, v.y, u.x, u.y);
    mma16816(q1, u.x, v.x, u.y, v.y, v.x, v.y);
    mma16816(q2, u.z, v.z, u.w, v.w, u.z, u.w);
    mma16816(q3, u.z, v.z, u.w, v.w, v.z, v.w);
    mma16816(s0, u.x, v.x, u.y, v.y, one, one);
    mma16816(s1, u.z, v.z, u.w, v.w, one, one);
  }
  if (t4 == (g >> 1)) {
    const float r0 = (s0[0] + s1[0]) * (1.f / D_), r1 = (s0[2] + s1[2]) * (1.f / D_);
    const float v0 = ((g & 1) ? q0[1] + q2[1] : q0[0] + q2[0]) * (1.f / D_) - r0 * r0;
    const float v1 = ((g & 1) ? q1[3] + q3[3] : q1[2] + q3[2]) * (1.f / D_) - r1 * r1;
    if (g < nrows) stg128(stat + g, __float_as_uint(m0), __float_as_uint(rsqrt_fast(fmaxf(v0, 0.f) + 1e-5f)), ep, 0u);
    if (g + 8 < nrows) stg128(stat + g + 8, __float_as_uint(m1), __float_as_uint(rsqrt_fast(fmaxf(v1, 0.f) + 1e-5f)), ep, 0u);
  }
}

struct KvJob { uint2 kk[11], vv[8]; uint4 s0, s1; };
__device__ __forceinline__ void kv_load(const Params& P, int unit, int lane, KvJob& J) {
  const int t0 = (unit & 127) * 16 + (lane >> 4) * 8, c = (unit >> 7) * 64 + (lane & 15) * 4;
  const __nv_bfloat16* kp = P.k + (size_t)t0 * D_ + c;
  const __nv_bfloat16* vp = P.v + (size_t)t0 * D_ + c;
#pragma unroll
  for (int j = 0; j < 11; j++) { J.kk[j] = make_uint2(0u, 0u); if (j >= 3 || t0 > 0) J.kk[j] = ldg64(kp + (j - 3) * D_); }
#pragma unroll
  for (int j = 0; j < 8; j++) J.vv[j] = ldg64(vp + j * D_);
  J.s0 = __ldg((const uint4*)(P.shift + c * 4)); J.s1 = __ldg((const uint4*)(P.shift + c * 4 + 8));
}
__device__ __forceinline__ void kv_finish(const KvJob& J, uint32_t a, int d1, int d2, int d3) {
  const uint32_t wa[4] = {__byte_perm(J.s0.x, J.s0.z, 0x5410), __byte_perm(J.s0.x, J.s0.z, 0x7632), __byte_perm(J.s0.y, J.s0.w, 0x5410), __byte_perm(J.s0.y, J.s0.w, 0x7632)};
  const uint32_t wb[4] = {__byte_perm(J.s1.x, J.s1.z, 0x5410), __byte_perm(J.s1.x, J.s1.z, 0x7632), __byte_perm(J.s1.y, J.s1.w, 0x5410), __byte_perm(J.s1.y, J.s1.w, 0x7632)};
  uint32_t ra[8], rb[8];
#pragma unroll
  for (int j = 0; j < 8; j++) {
    ra[j] = hmul2(hfma2(J.kk[j + 3].x, wa[0], hfma2(J.kk[j + 2].x, wa[1], hfma2(J.kk[j + 1].x, wa[2], hmul2(J.kk[j].x, wa[3])))), J.vv[j].x);
    rb[j] = hmul2(hfma2(J.kk[j + 3].y, wb[0], hfma2(J.kk[j + 2].y, wb[1], hfma2(J.kk[j + 1].y, wb[2], hmul2(J.kk[j].y, wb[3])))), J.vv[j].y);
  }
  const uint32_t* src[4] = {ra, ra, rb, rb};
  const int off[4] = {0, d1, d2, d3};
#pragma unroll
  for (int c = 0; c < 4; c++) {
    const uint32_t sel = (c & 1) ? 0x7632 : 0x5410, *r = src[c];
    const uint32_t w0 = __byte_perm(r[7], r[6], sel), w1 = __byte_perm(r[5], r[4], sel), w2 = __byte_perm(r[3], r[2], sel), w3 = __byte_perm(r[1], r[0], sel);
    sts128(a + off[c], w0, w1, w2, w3);
  }
}

template <int J> __device__ __forceinline__ void ldp(uint32_t* p, uint32_t pa) {
  p[0] = lds32(pa + 256 * J); p[1] = lds32(pa + 256 * J + 128); p[2] = lds32(pa + 256 * J + 16); p[3] = lds32(pa + 256 * J + 144);
}
template <int J, int BASE> __device__ __forceinline__ void cstep(float (&d)[64], const uint32_t* a, uint32_t db) {
  if (BASE + 96 < 256 - 16 * J) wg_rs32<48, (J != 0)>(d, a, db + (J * 16 + BASE + 96));
  if (BASE + 64 < 256 - 16 * J) wg_rs32<32, (J != 0)>(d, a, db + (J * 16 + BASE + 64));
  if (BASE + 32 < 256 - 16 * J) wg_rs32<16, (J != 0)>(d, a, db + (J * 16 + BASE + 32));
  if (BASE < 256 - 16 * J) wg_rs32<0, (J != 0)>(d, a, db + (J * 16 + BASE));
}
template <int JN> __device__ __forceinline__ void csend(float (&d)[64], uint32_t sa, uint32_t carry, bool sh) {
  constexpr int JL = JN & 15;
  float v0 = d[4 * JL], v1 = d[4 * JL + 1];
  if (JL < 15) { v0 += d[4 * JL + 6]; v1 += d[4 * JL + 7]; }
  uint32_t v = pack2(v0, v1);
  if (JN == 15) v = hadd2(v, carry);
  if (JN == 0) sts32p(sa, v, !sh); else sts32(sa + JN * 128, v);
}
#define CSEND8(B, CARRY) csend<B + 7>(d, sa, CARRY, sh); csend<B + 6>(d, sa, 0, sh); csend<B + 5>(d, sa, 0, sh); csend<B + 4>(d, sa, 0, sh); \
                         csend<B + 3>(d, sa, 0, sh); csend<B + 2>(d, sa, 0, sh); csend<B + 1>(d, sa, 0, sh); csend<B>(d, sa, 0, sh)

__device__ __forceinline__ void conv_issue_u(const Params& P, int ch, uint32_t dst, uint32_t bar, unsigned ep, unsigned seen = 0) {
  if ((int)(seen - ep * 128) < 0) flag_wait(P.s->cnt, C_KV + (ch >> 6), ep * 128);
  fence_async();
  mbar_expect(bar, 4096);
  bulk_g2s(dst, P.s->ur + (size_t)ch * S_, 4096, bar);
}

struct HJob { uint4 v0, v1; uint32_t n0, n1, dv; };
__device__ __forceinline__ void h_load(const Params& P, int ch, int c0, HJob& H) {
  const __nv_bfloat16* hp = P.h + (size_t)ch * S_ + c0 * 8;
  H.v0 = ldg128(hp); H.v1 = ldg128(hp + 256);
  H.n0 = ldg32(hp + 8); H.n1 = 0;
  if (c0 + 33 < 256) H.n1 = ldg32(hp + 264);
  H.dv = 0;
  if (c0 == 0) asm volatile("ld.global.nc.u16 %0, [%1];" : "=r"(H.dv) : "l"(P.dv + ch));
}
__device__ __forceinline__ void h_store(uint32_t st, int c0, HJob& H) {
  H.v0.x = __byte_perm(pack2(bf_lo(H.v0.x) + bf_lo(H.dv), 0.f), H.v0.x, 0x7610);
  if (c0 == 0) sts128(st + ST_H1, 0, 0, 0, H.v0.x << 16);
  sts128(st + ST_H0 + 16 + 16 * c0, H.v0.x, H.v0.y, H.v0.z, H.v0.w);
  sts128(st + ST_H1 + 16 + 16 * c0, __byte_perm(H.v0.x, H.v0.y, 0x5432), __byte_perm(H.v0.y, H.v0.z, 0x5432), __byte_perm(H.v0.z, H.v0.w, 0x5432), __byte_perm(H.v0.w, H.n0, 0x5432));
  sts128(st + ST_H0 + 528 + 16 * c0, H.v1.x, H.v1.y, H.v1.z, H.v1.w);
  sts128(st + ST_H1 + 528 + 16 * c0, __byte_perm(H.v1.x, H.v1.y, 0x5432), __byte_perm(H.v1.y, H.v1.z, 0x5432), __byte_perm(H.v1.z, H.v1.w, 0x5432), __byte_perm(H.v1.w, H.n1, 0x5432));
}
__device__ __forceinline__ void zero_pads(uint32_t st, int nst, int tid) {
  if (tid < 25 * nst) sts128(st + (tid >= 25 ? ST_BYTES - 400 : 0) + 4096 + tid * 16, 0, 0, 0, 0);
}
__device__ __forceinline__ void zero_xch(uint32_t xa, int l) { sts128(xa + (l >> 3) * 4096 + 3968 + (l & 7) * 16, 0, 0, 0, 0); }

__device__ __forceinline__ void conv_run(const Params& P, int ch0, int ch1, int ch2, int ch3, int nloc, uint32_t ux, int n, uint32_t xa, uint32_t yb, uint32_t st0, int nst, uint32_t ubar,
                                         int barid, unsigned ep, int warp, int lane) {
  const int g = lane >> 2, t4 = lane & 3;
  const int y0 = 16 * warp - 7 + g + 2 * t4;
  const uint32_t poff = (g & 1) ? (ST_H0 + 16 + y0 * 2) : (ST_H1 + 16 + (y0 - 1) * 2);
  const bool sh = t4 < warp;
  const uint32_t sa = xa + warp * 4096 + (lane & ~3) * 4 + (((t4 - warp) & 3) << 2) - (sh ? 128 : 0);
  const uint32_t rb = xa + warp * 1024 + lane * 4;
  const uint32_t ya = yb + (255 - (64 * warp + lane)) * 16;
  const int c0 = warp * 64 + lane;
  float d[64];
  int ch = ch0;
#pragma unroll 1
  for (int m = 0; m < n; m++) {
    const int nch = m == 0 ? ch1 : m == 1 ? ch2 : ch3;
    const int s = m & (nst - 1), s1 = (m + 1) & (nst - 1);
    const uint32_t st = st0 + s * ST_BYTES, st1 = st0 + s1 * ST_BYTES;
    HJob H;
    unsigned fl = 0;
    if (m + 1 < n) {
      h_load(P, nch, c0, H);
      asm volatile("ld.relaxed.gpu.global.u32 %0, [%1];" : "=r"(fl) : "l"(P.s->cnt + (C_KV + (nch >> 6)) * 32) : "memory");
    }
    const uint32_t db = (((m == 2 && nloc == 3 ? ux : st + ST_U) & 0x3FFFF) >> 4) | (1u << 16);
    const uint32_t pa = st + poff;
    uint32_t p[32];
    ldp<0>(p, pa); ldp<1>(p + 4, pa); ldp<2>(p + 8, pa); ldp<3>(p + 12, pa);
    if (m < 1 || m >= nloc) mbar_wait(ubar + 8 * s, nst == 2 ? (m == 2) : m & 1);
    wg_fence(); cstep<0, 128>(d, p, db); cstep<1, 128>(d, p + 4, db); cstep<2, 128>(d, p + 8, db); cstep<3, 128>(d, p + 12, db); wg_commit();
    ldp<4>(p + 16, pa); ldp<5>(p + 20, pa); ldp<6>(p + 24, pa); ldp<7>(p + 28, pa);
    wg_fence(); cstep<4, 128>(d, p + 16, db); cstep<5, 128>(d, p + 20, db); cstep<6, 128>(d, p + 24, db); cstep<7, 128>(d, p + 28, db); wg_commit();
    wg_wait<1>();
    CSEND8(24, 0);
    wg_wait<0>();
    CSEND8(16, 0);
    const uint32_t carry = pack2(d[2], d[3]);
    wg_fence(); cstep<0, 0>(d, p, db); cstep<1, 0>(d, p + 4, db); cstep<2, 0>(d, p + 8, db); cstep<3, 0>(d, p + 12, db); wg_commit();
    cstep<4, 0>(d, p + 16, db); cstep<5, 0>(d, p + 20, db); cstep<6, 0>(d, p + 24, db); cstep<7, 0>(d, p + 28, db); wg_commit();
    if (warp == 1 && m == 0 && nloc == 2 && elect()) { bulk_wait<0>(); flag_add_relaxed(P.s->cnt, C_INIT); }
    if (warp == 0 && elect()) {
      bulk_wait_read<0>();
      if (nst == 2 && m + 1 < n && m + 1 >= nloc) conv_issue_u(P, nch, st1 + ST_U, ubar + 8 * s1, ep, fl);
    }
    wg_wait<1>();
    ldp<8>(p, pa); ldp<9>(p + 4, pa); ldp<10>(p + 8, pa); ldp<11>(p + 12, pa);
    wg_fence(); cstep<8, 0>(d, p, db); cstep<9, 0>(d, p + 4, db); cstep<10, 0>(d, p + 8, db); cstep<11, 0>(d, p + 12, db); wg_commit();
    wg_wait<1>();
    ldp<12>(p + 16, pa); ldp<13>(p + 20, pa); ldp<14>(p + 24, pa); ldp<15>(p + 28, pa);
    wg_fence(); cstep<12, 0>(d, p + 16, db); cstep<13, 0>(d, p + 20, db); cstep<14, 0>(d, p + 24, db); cstep<15, 0>(d, p + 28, db); wg_commit();
    wg_wait<1>();
    CSEND8(8, carry);
    wg_wait<0>();
    if (nst == 1 && n == 3 && m == 1) bar_arrive(12, 256);
    CSEND8(0, 0);
    bar_sync(barid, 128);
    if (warp == 0 && nst == 1 && m + 1 < n && elect()) conv_issue_u(P, nch, st + ST_U, ubar, ep, fl);
    uint32_t y[8];
#pragma unroll
    for (int q = 0; q < 8; q++) {
      const uint32_t r0 = lds32(rb + q * 128), r1 = lds32(rb + 4096 + q * 128), r2 = lds32(rb + 8192 + q * 128), r3 = lds32(rb + 12288 + q * 128);
      y[q] = hadd2(hadd2(r0, r1), hadd2(r2, r3));
    }
    stsm4t(ya, y[0], y[1], y[2], y[3]);
    stsm4t(ya - 512, y[4], y[5], y[6], y[7]);
    if (m + 1 < n) h_store(st1, c0, H);
    fence_async_smem();
    bar_sync(barid, 128);
    if (warp == 0 && elect()) { bulk_s2g(P.s->yt + (size_t)ch * S_, yb, 4096); bulk_commit(); }
    ch = nch;
  }
  if (warp == 0) {
    if (elect()) bulk_wait<0>();
    __syncwarp();
    if (lane < n) flag_add_relaxed(P.s->cnt, C_Y + ((lane == 0 ? ch0 : lane == 1 ? ch1 : lane == 2 ? ch2 : ch3) >> 7));
  }
}

__global__ void __cluster_dims__(2, 1, 1) __launch_bounds__(NTHR, 1)
fused_kernel(const Params P, const __grid_constant__ CUtensorMap tm_x, const __grid_constant__ CUtensorMap tm_x64,
             const __grid_constant__ CUtensorMap tm_w1, const __grid_constant__ CUtensorMap tm_w2,
             const __grid_constant__ CUtensorMap tm_out, const __grid_constant__ CUtensorMap tm_yt,
             const __grid_constant__ CUtensorMap tm_k8, const __grid_constant__ CUtensorMap tm_v8,
             const __grid_constant__ CUtensorMap tm_ur) {
  const uint32_t sb = smem_u32(smem_raw);
  const uint32_t bars = sb + OFF_BAR;
  const int wgi = __shfl_sync(~0u, threadIdx.x >> 7, 0), warp = __shfl_sync(~0u, (threadIdx.x >> 5) & 3, 0), lane = threadIdx.x & 31;
  const int cl = blockIdx.x >> 1, rank = blockIdx.x & 1;
  const bool is_conv = cl >= CONV_CL0 && cl < CONV_CL0 + CONV_NCL;
  const int ci = blockIdx.x - 2 * CONV_CL0;
  const int mc = cl < CONV_CL0 ? cl : cl - CONV_NCL;
  const int f = mc >> 3, mt = 2 * (mc & 7) + rank;
  const int mi = 2 * mc + rank;

  if (wgi == 1 && warp == 3) asm volatile("prefetch.global.L2 [%0];" :: "l"(lane < 10 ? P.b2 + lane * 64 : P.b1 + (lane - 10) * 64));
  if (wgi == 0 && warp == 0 && elect()) {
    mbar_init(bars + 8 * B_WF, 1);
    if (!is_conv) {
      mbar_expect(bars + 8 * B_WF, 49152);
      tma_ld(sb + OFF_X, &tm_x, 0, mt * 128, bars + 8 * B_WF);
      tma_ld3(sb + OFF_W, &tm_w1, 0, f * 4, bars + 8 * B_WF);
      tma_ld3(sb + OFF_W + 16384, &tm_w1, 0, f * 4 + 2, bars + 8 * B_WF);
    }
    if (is_conv) {
      mbar_init(bars + 8 * (B_KV + 1), 1); mbar_init(bars + 8 * B_LN, 1);
      const int p0 = ci * 3 < 52 ? 30 * ci : 52 + 27 * ci, p1 = ci * 3 + 3 < 52 ? 30 * ci + 30 : 52 + 27 * ci + 27;
      mbar_expect(bars + 8 * B_LN, (p1 - p0) * 2560);
      bulk_g2s(sb + CV_LN, P.x + (size_t)p0 * 2 * D_, (p1 - p0) * 2560, bars + 8 * B_LN);
      mbar_expect(bars + 8 * B_KV, 32768);
      tma_ld3x(sb, &tm_k8, ci * 8, 0, bars + 8 * B_KV);
      tma_ld3x(sb + 32768, &tm_v8, ci * 8, 0, bars + 8 * B_KV);
      mbar_expect(bars + 8 * (B_KV + 1), 32768);
      tma_ld3x(sb + 16384, &tm_k8, ci * 8, 128, bars + 8 * (B_KV + 1));
      tma_ld3x(sb + 49152, &tm_v8, ci * 8, 128, bars + 8 * (B_KV + 1));
    }
#pragma unroll
    for (int b = 1; b < B_NUM; b++) if (b > B_LN || !is_conv) mbar_init(bars + 8 * b, b >= B_WE && b < B_BEXT ? 4 : b == B_XT ? 2 : 1);
  }
  asm volatile("fence.mbarrier_init.release.cluster;" ::: "memory");
  __syncthreads();
  cluster_arrive();

  if (is_conv || wgi == 2) {
    const int tid = warp * 32 + lane;
    const uint32_t xa = is_conv ? sb + CV_X + wgi * 16384 : sb + OFF_C, yb = is_conv ? sb + CV_Y + wgi * 4096 : xa + 16384;
    const uint32_t st0 = is_conv ? sb + CV_ST + wgi * 2 * ST_BYTES : xa + 20480, ubar = bars + 8 * (B_U + (is_conv ? 2 * wgi : 0));
    const int ch0 = is_conv ? ci * 8 + wgi : 432 + mi;
    const int ch1 = is_conv ? ch0 + 3 : ch0 + 96, ch2 = is_conv ? (wgi < 2 ? ch0 + 6 : 288 + ci) : ch0 + 112, ch3 = 324 + 3 * ci + wgi;
    cluster_wait();
    zero_pads(st0, is_conv ? 2 : 1, tid);
    if (is_conv && wgi == 2 && tid >= 64 && tid < 112) sts128(sb + CV_UX + (tid >= 88 ? ST_H0 - 384 : 0) + 4096 + (tid - 64) * 16, 0, 0, 0, 0);
    fence_async_smem();
    unsigned ep;
    asm volatile("ld.relaxed.gpu.global.u32 %0, [%1];" : "=r"(ep) : "l"(P.s->cnt + C_EPOCH * 32) : "memory");
    HJob H;
    KvJob K, K1;
    const int unit = 512 + warp * 96 + mi;
    if (is_conv) {
      const int p0 = ci * 3 < 52 ? 30 * ci : 52 + 27 * ci, p1 = ci * 3 + 3 < 52 ? 30 * ci + 30 : 52 + 27 * ci + 27;
      h_load(P, ch0, warp * 64 + lane, H);
      if (wgi < 2) {
        const __nv_bfloat16* tp = P.shift + ci * 32;
        K.s0 = __ldg((const uint4*)tp); K.s1 = __ldg((const uint4*)(tp + 8)); K1.s0 = __ldg((const uint4*)(tp + 16)); K1.s1 = __ldg((const uint4*)(tp + 24));
        h_store(st0, warp * 64 + lane, H);
        ep = __shfl_sync(~0u, ep, 0) + 1;
        mbar_wait(bars + 8 * B_KV, 0);
        if (wgi) mbar_wait(bars + 8 * (B_KV + 1), 0);
        const uint32_t ka = sb + wgi * 16384 + tid * 16, kp = tid ? ka - 16 : sb + 127 * 16;
#pragma unroll
        for (int j = 0; j < 11; j++) {
          uint4 t = lds128(j < 3 ? kp + (5 + j) * 2048 : ka + (j - 3) * 2048);
          if (j < 3 && tid + wgi == 0) t = make_uint4(0u, 0u, 0u, 0u);
          K.kk[j] = make_uint2(t.x, t.y); K1.kk[j] = make_uint2(t.z, t.w);
        }
#pragma unroll
        for (int j = 0; j < 8; j++) { const uint4 t = lds128(ka + 32768 + j * 2048); K.vv[j] = make_uint2(t.x, t.y); K1.vv[j] = make_uint2(t.z, t.w); }
        const uint32_t ua = sb + CV_ST + (255 - wgi * 128 - tid) * 16;
        kv_finish(K, ua, 2 * ST_BYTES, 4 * ST_BYTES, ST_BYTES);
        kv_finish(K1, ua + 3 * ST_BYTES, 2 * ST_BYTES, CV_UX - CV_ST - 3 * ST_BYTES, CV_UX - CV_ST - 3 * ST_BYTES + ST_H0);
        fence_async_smem();
        bar_sync(11, 256);
        if (wgi == 1 && warp < 3) zero_xch(sb + CV_X + warp * 16384, lane);
        bar_sync(10, 384);
        if (tid < 3 && wgi == 0) mbar_arrive(bars + 8 * (B_U + 2 * tid));
      } else {
        h_store(st0, warp * 64 + lane, H);
        ep = __shfl_sync(~0u, ep, 0) + 1;
        mbar_wait(bars + 8 * B_LN, 0);
        ln_rows(sb + CV_LN + warp * 16 * 1280, P.s->stats + 2 * p0 + warp * 16, 2 * (p1 - p0) - warp * 16, ep, lane);
        bar_arrive(10, 384);
        bar_sync(1 + wgi, 128);
        if (warp == 1) {
          if (elect()) { bulk_s2g(P.out + (size_t)p0 * 2 * D_, sb + CV_LN, (p1 - p0) * 2560); bulk_commit(); }
          __syncwarp();
        }
      }
    } else {
      {
        if (warp == 3) {
          const uint4 b = __ldg((const uint4*)(P.b1 + f * 256 + lane * 8));
          const uint32_t ba = xa + (lane >> 3) * 2048, l7 = lane & 7;
#pragma unroll
          for (int r = 6; r < 16; r++) sts128(ba + r * 128 + (l7 << 4), 0, 0, 0, 0);
          sts128(ba + 3 * 128 + ((l7 ^ 3) << 4), b.x, b.y, b.z, b.w);
          sts128(ba + 4 * 128 + ((l7 ^ 4) << 4), b.x, b.y, b.z, b.w);
          sts32(bars + 8 * B_NUM, ep + 1);
          if (lane == 0) map_prefetch(&tm_ur);
          fence_async_smem();
          __syncwarp();
          if (lane == 0) mbar_arrive(bars + 8 * B_BEXT);
        }
        mbar_wait(bars + 8 * (B_WF + J3_GATE), 0);
        const __nv_bfloat16* wp = P.w1 + (size_t)(mt * 40 + warp * 10) * F_ + f * 256 + lane * 8;
        uint4 w[10];
#pragma unroll
        for (int j = 0; j < 10; j++) w[j] = ldg128(wp + j * F_);
        float a[8] = {0.f, 0.f, 0.f, 0.f, 0.f, 0.f, 0.f, 0.f};
#pragma unroll
        for (int j = 0; j < 10; j++) {
          a[0] += bf_lo(w[j].x); a[1] += bf_hi(w[j].x); a[2] += bf_lo(w[j].y); a[3] += bf_hi(w[j].y);
          a[4] += bf_lo(w[j].z); a[5] += bf_hi(w[j].z); a[6] += bf_lo(w[j].w); a[7] += bf_hi(w[j].w);
        }
        ep = __shfl_sync(~0u, ep, 0) + 1;
        float* cp = (float*)(P.s->cs + (((ep & 1) * 4 + warp) * 6 + f) * 96 + lane);
        red4f(cp, a[0], a[1], a[2], 1.f); red4f(cp + 128, a[3], a[4], a[5], 1.f); red4f(cp + 256, a[6], a[7], 0.f, 1.f);
        kv_load(P, unit, lane, K);
        kv_load(P, unit + 384, lane, K1);
        h_load(P, ch0, warp * 64 + lane, H);
      }
      {
        const uint32_t s0 = xa + 8192 + warp * 2048, s1 = xa + 16384 + warp * 2048, lo = (lane & 15) * 32 + (lane < 16 ? 16 : 0);
        kv_finish(K, s0 + lo, 512, 1024, 1536);
        kv_finish(K1, s1 + lo, 512, 1024, 1536);
        h_store(st0, warp * 64 + lane, H);
        fence_async_smem();
        __syncwarp();
        if (elect()) {
          tma_st3(&tm_ur, S_ - 16 - (unit & 127) * 16, (unit >> 7) * 16, s0);
          tma_st3(&tm_ur, S_ - 16 - (unit & 127) * 16, (unit >> 7) * 16 + 48, s1);
          bulk_commit();
          bulk_wait<0>();
          flag_add_relaxed(P.s->cnt, C_KV + (unit >> 7)); flag_add_relaxed(P.s->cnt, C_KV + 3 + (unit >> 7));
        }
        bar_sync(1 + wgi, 128);
        if (warp == 2) zero_xch(xa, lane);
      }
      if (warp == 0 && elect()) {
        map_prefetch(&tm_out); map_prefetch(&tm_yt); map_prefetch(&tm_x64);
        conv_issue_u(P, ch0, st0 + ST_U, ubar, ep, ep * 128 - 1);
      }
      if (warp == 1 && mi < 4) {
#pragma unroll 1
        for (int i = lane; i < 576; i += 32) P.s->cs[((ep + 1) & 1) * 2304 + mi * 576 + i] = make_float4(0.f, 0.f, 0.f, 0.f);
      }
      if (warp == 2 && lane == 0) { flag_wait(P.s->cnt, C_INIT, ep * 36); mbar_arrive(bars + 8 * B_INIT); }
      bar_sync(6, 384);
    }
    if (is_conv && CSTAG) __nanosleep(wgi * CSTAG);
    conv_run(P, ch0, ch1, ch2, ch3, is_conv ? (wgi < 2 ? 3 : 2) : 0, sb + CV_UX + wgi * ST_H0, is_conv ? 4 : (f == 5 ? 3 : 2), xa, yb, st0,
             is_conv ? 2 : 1, ubar, 1 + wgi, ep, warp, lane);
    if (!is_conv && f < 5) {
      bar_sync(1 + wgi, 128);
      if (warp == 0 && elect()) {
        flag_wait(P.s->cnt, C_Y + f, ep * 128);
        fence_async();
        mbar_expect(bars + 8 * B_Y, 32768);
        tma_ld(sb + OFF_C, &tm_yt, mt * 128, f * 128, bars + 8 * B_Y);
        tma_ld(sb + OFF_C + 16384, &tm_yt, mt * 128 + 64, f * 128, bars + 8 * B_Y);
      }
    }
    if (blockIdx.x == NCTA - 1 && tid == 0) {
#pragma unroll 1
      for (int i = 0; i < 5; i++) flag_wait(P.s->cnt, C_Y + i, ep * 128);
      flag_add_relaxed(P.s->cnt, C_EPOCH);
    }
  } else {
    const int w = wgi, tid = warp * 32 + lane, g = lane >> 2, t4 = lane & 3;
    auto chunk_of = [&](int qi) { int q = f + 1 + qi; return f == 5 ? qi : q >= 5 ? q - 5 : q; };
    auto load_stage = [&](int v) {
      const uint32_t sl = v & 3, fb = bars + 8 * (B_WF + sl), dst = sb + OFF_W + sl * 32768 + rank * 16384;
      if (v >= 4) mbar_wait(bars + 8 * (B_WE + sl), ((v >> 2) - 1) & 1);
      if (elect()) {
        if (v < 10) {
          mbar_expect(fb, 49152);
          tma_ld3_mc(dst, &tm_w1, v * 64, f * 4 + rank * 2, fb);
          tma_ld(sb + OFF_X + sl * 16384, &tm_x, v * 64, mt * 128, fb);
        } else {
          mbar_expect(fb, 32768);
          tma_ld3_mc(dst, &tm_w2, f * 256 + (v & 1) * 128, chunk_of((v - 10) >> 1) * 2 + rank, fb);
        }
      }
      __syncwarp();
    };
    const uint32_t we_l = bars + 8 * B_WE, we_r = mapa(we_l, rank ^ 1);
    auto release = [&](uint32_t sl) { if (warp == 0 && elect()) { mbar_arrive(we_l + 8 * sl); mbar_arrive_cl(we_r + 8 * sl); } };
    cluster_wait();
    if (w == 1 && warp == 0) {
#pragma unroll 1
      for (int v = 1; v < 4; v++) { if (v == FIRST_GATE) mbar_wait(bars + 8 * B_WF, 0); load_stage(v); }
    }
    uint32_t hf[64];
    {
      float d[128];
      const uint32_t xlo = ((sb + OFF_X + w * 8192) & 0x3FFFF) >> 4;
      const uint32_t wlo = (((sb + OFF_W) & 0x3FFFF) >> 4) | (512u << 16);
      auto issue = [&](int v) {
        const uint32_t sl = v & 3;
        mbar_wait(bars + 8 * (B_WF + sl), (v >> 2) & 1);
        const uint32_t a = xlo + sl * 1024, b = wlo + sl * 2048;
        wg_fence();
        wg_ss256(d, a, b, v != 0);
        wg_ss256(d, a + 2, b + 128, 1);
        wg_ss256(d, a + 4, b + 256, 1);
        wg_ss256(d, a + 6, b + 384, 1);
        wg_commit();
      };
      auto retire = [&](int v) {
        wg_wait<1>();
        if (v > 0) {
          release((v - 1) & 3);
          if (w == 1 && warp == 0) load_stage(v + 3);
        }
      };
#pragma unroll 1
      for (int v = 0; v < EXTV; v++) {
        issue(v);
        if (v == W2PF && w == 0 && warp == 1 && (mc & 7) < 5 && elect()) {
          tma_prefetch3(&tm_w2, f * 256, (mc & 7) * 2 + rank); tma_prefetch3(&tm_w2, f * 256 + 128, (mc & 7) * 2 + rank);
        }
        retire(v);
      }
      issue(EXTV);
      mbar_wait(bars + 8 * B_BEXT, 0);
      const unsigned ep = lds32(bars + 8 * B_NUM);
      const float4* sp = P.s->stats + mt * 128 + w * 64 + warp * 16 + g;
      const float4* cq = P.s->cs + (((ep & 1) * 4 + 2 * (tid & 1)) * 6 + f) * 96 + w * 48 + (tid < 96 ? tid >> 1 : 0);
      float4 sa = ld_relaxed4(sp), sc = ld_relaxed4(sp + 8), v0 = ld_relaxed4(cq), v1 = ld_relaxed4(cq + 576);
      retire(EXTV);
      issue(EXTV + 1);
      uint32_t e0, e1;
      {
#pragma unroll 1
        for (int n = 0; n < 400000; n++) {
          if (__all_sync(~0u, v0.w + v1.w == 32.f && __float_as_uint(sa.z) == ep && __float_as_uint(sc.z) == ep && sa.w == sc.w)) break;
          sa = ld_relaxed4(sp); sc = ld_relaxed4(sp + 8); v0 = ld_relaxed4(cq); v1 = ld_relaxed4(cq + 576);
        }
          float4 u = make_float4(v0.x + v1.x, v0.y + v1.y, v0.z + v1.z, 0.f);
          u.x += __shfl_xor_sync(~0u, u.x, 1); u.y += __shfl_xor_sync(~0u, u.y, 1); u.z += __shfl_xor_sync(~0u, u.z, 1);
          if (tid < 96) {
            const int i = w * 48 + (tid >> 1), l = i & 31, p = i >> 5;
            const uint32_t h01 = pack2(-u.x, -u.y), h2 = pack2(-u.z, 0.f);
            uint32_t e01 = h01, e2 = h2;
            if (tid & 1) { e01 = pack2(-u.x - bf_lo(h01), -u.y - bf_hi(h01)); e2 = pack2(-u.z - bf_lo(h2), 0.f); }
            const uint32_t ba = sb + OFF_C + (l >> 3) * 2048 + p * 6;
#pragma unroll
            for (int q = 0; q < 2; q++) {
              const uint32_t r = (tid & 1) ? 1 + 4 * q : 2 * q, a = ba + r * 128 + (((l & 7) ^ r) << 4);
              asm volatile("st.shared.u16 [%0], %1;" :: "r"(a), "h"((uint16_t)e01) : "memory");
              asm volatile("st.shared.u16 [%0], %1;" :: "r"(a + 2), "h"((uint16_t)(e01 >> 16)) : "memory");
              if (p < 2) asm volatile("st.shared.u16 [%0], %1;" :: "r"(a + 4), "h"((uint16_t)e2) : "memory");
            }
          }
          if (t4 == 0) {
            asm volatile("st.shared.v2.f32 [%0], {%1,%2};" :: "r"(sb + OFF_STAT + (w * 64 + warp * 16 + g) * 8), "f"(sa.x), "f"(sa.y) : "memory");
            asm volatile("st.shared.v2.f32 [%0], {%1,%2};" :: "r"(sb + OFF_STAT + (w * 64 + warp * 16 + g + 8) * 8), "f"(sc.x), "f"(sc.y) : "memory");
          }
          fence_async_smem();
          const float da = rcp_fast(sa.y), dc = rcp_fast(sc.y);
          const float mha = bf_round(sa.x), mhc = bf_round(sc.x), dha = bf_round(da), dhc = bf_round(dc);
          const float x0 = t4 == 0 ? mha : t4 == 1 ? sa.x - mha : da - dha, x1 = t4 == 0 ? mha : t4 == 1 ? dha : sa.x - mha;
          const float y0 = t4 == 0 ? mhc : t4 == 1 ? sc.x - mhc : dc - dhc, y1 = t4 == 0 ? mhc : t4 == 1 ? dhc : sc.x - mhc;
          e0 = t4 == 3 ? 0u : pack2(x0, x1); e1 = t4 == 3 ? 0u : pack2(y0, y1);
      }
      retire(EXTV + 1);
#pragma unroll 1
      for (int v = EXTV + 2; v < 10; v++) { issue(v); retire(v); }
      bar_sync(5, 256);
      wg_fence();
      wg_rs256(d, e0, e1, 0u, 0u, (((sb + OFF_C) & 0x3FFFF) >> 4) | (128u << 16), 1);
      wg_commit();
      wg_wait<0>();
      bar_arrive(6, 384);
      release(1);
      if (w == 1 && warp == 0) load_stage(13);
      const float k0 = 0.7978845608028654f, k1 = 0.7978845608028654f * 0.044715f;
      const float ra = lds64f(sb + OFF_STAT + (w * 64 + warp * 16 + g) * 8).y, rc = lds64f(sb + OFF_STAT + (w * 64 + warp * 16 + g + 8) * 8).y;
      const float h0 = 0.5f * ra, c10 = k0 * ra, c30 = k1 * ra * ra * ra;
      const float h1 = 0.5f * rc, c11 = k0 * rc, c31 = k1 * rc * rc * rc;
#pragma unroll
      for (int i = 0; i < 64; i++) {
        const float hh = (i & 1) ? h1 : h0, c1 = (i & 1) ? c11 : c10, c3 = (i & 1) ? c31 : c30;
        const float a = d[2 * i], b = d[2 * i + 1];
        const float ta = tanh_fast(a * fmaf(a * a, c3, c1)), tb = tanh_fast(b * fmaf(b * b, c3, c1));
        const float pa = a * hh, pb = b * hh;
        hf[i] = pack2(fmaf(pa, ta, pa), fmaf(pb, tb, pb));
      }
    }
    {
      float d[64];
      const uint32_t wlo = (((sb + OFF_W) & 0x3FFFF) >> 4) | (1024u << 16);
      const uint32_t sta = sb + OFF_X + w * 32768 + (warp * 16 + (lane & 15)) * 128;
      const int l7 = lane & 7;
#pragma unroll 1
      for (int qi = 0; qi < 5; qi++) {
        const int q = chunk_of(qi);
        const uint32_t hb = ((qi + 1) & 1) * 2, ph = ((qi + 5) >> 1) & 1;
        if (w == 1) bar_sync(7 + 2 * (qi & 1), 256); else if (qi >= 1) bar_sync(8, 256); else if (f == 5) bar_sync(12, 256);
#pragma unroll
        for (int j = 0; j < 2; j++) {
          mbar_wait(bars + 8 * (B_WF + hb + j), ph);
          const uint32_t b = wlo + (hb + j) * 2048;
          wg_fence();
#pragma unroll
          for (int kk = 0; kk < 8; kk++) wg_rs128(d, &hf[32 * j + 4 * kk], b + 128 * kk, j + kk != 0);
          wg_commit();
          if (j == 0 && w == 0 && warp == 0 && qi >= 1 && qi < 4) load_stage(13 + 2 * qi);
        }
        if (w == 0) bar_arrive(7 + 2 * (qi & 1), 256); else if (qi < 4) bar_arrive(8, 256);
        wg_wait<1>();
        if (qi < 3) { release(hb); if (w == 1 && warp == 0) load_stage(14 + 2 * qi); }
        wg_wait<0>();
        if (qi < 3) release(hb + 1);
        if (qi == 0) { mbar_wait(we_l + 8, 0); mbar_wait(bars + 8 * B_INIT, 0); fence_async(); }
        const uint32_t st = sta + (qi & 1) * 16384;
        if (qi == 4 && f < 5) {
          const float2 s0 = lds64f(sb + OFF_STAT + (w * 64 + warp * 16 + g) * 8), s1 = lds64f(sb + OFF_STAT + (w * 64 + warp * 16 + g + 8) * 8);
          const uint32_t ma = pack2(s0.x, s0.x), ra = pack2(s0.y, s0.y), mb = pack2(s1.x, s1.x), rb = pack2(s1.y, s1.y);
          const uint32_t ya = sb + OFF_C + w * 16384 + (8 * (lane >> 4) + l7) * 128 + (((2 * warp + ((lane >> 3) & 1)) ^ l7) << 4);
          mbar_wait(bars + 8 * B_XT, 0);
#pragma unroll
          for (int cp = 0; cp < 8; cp++) {
            uint32_t xr[4];
            ldsm4(st + (cp >> 2) * 8192 + (((2 * (cp & 3) + (lane >> 4)) ^ l7) << 4), xr);
            const uint32_t b0 = ldg32(P.b2 + q * 128 + t4 * 2 + cp * 16), b1 = ldg32(P.b2 + q * 128 + t4 * 2 + cp * 16 + 8);
            hf[4 * cp] = hmul2(hsub2(xr[0], ma), ra); hf[4 * cp + 1] = hmul2(hsub2(xr[1], mb), rb);
            hf[4 * cp + 2] = hmul2(hsub2(xr[2], ma), ra); hf[4 * cp + 3] = hmul2(hsub2(xr[3], mb), rb);
            hf[32 + 4 * cp] = pack2(d[8 * cp] + bf_lo(b0), d[8 * cp + 1] + bf_hi(b0)); hf[33 + 4 * cp] = pack2(d[8 * cp + 2] + bf_lo(b0), d[8 * cp + 3] + bf_hi(b0));
            hf[34 + 4 * cp] = pack2(d[8 * cp + 4] + bf_lo(b1), d[8 * cp + 5] + bf_hi(b1)); hf[35 + 4 * cp] = pack2(d[8 * cp + 6] + bf_lo(b1), d[8 * cp + 7] + bf_hi(b1));
          }
          mbar_wait(bars + 8 * B_Y, 0);
#pragma unroll
          for (int cp = 0; cp < 8; cp++) {
            uint32_t yr[4];
            ldsm4t(ya + cp * 2048, yr);
            stsm4(st + (cp >> 2) * 8192 + (((2 * (cp & 3) + (lane >> 4)) ^ l7) << 4), hfma2(hf[4 * cp], yr[0], hf[32 + 4 * cp]), hfma2(hf[4 * cp + 1], yr[1], hf[33 + 4 * cp]),
                  hfma2(hf[4 * cp + 2], yr[2], hf[34 + 4 * cp]), hfma2(hf[4 * cp + 3], yr[3], hf[35 + 4 * cp]));
          }
        } else {
#pragma unroll
          for (int cp = 0; cp < 8; cp++) {
            const uint32_t a = st + (cp >> 2) * 8192 + (((2 * (cp & 3) + (lane >> 4)) ^ l7) << 4);
            stsm4(a, pack2(d[8 * cp], d[8 * cp + 1]), pack2(d[8 * cp + 2], d[8 * cp + 3]), pack2(d[8 * cp + 4], d[8 * cp + 5]), pack2(d[8 * cp + 6], d[8 * cp + 7]));
          }
        }
        fence_async_smem();
        if (warp == 0) bulk_wait_read<0>();
        bar_sync(1 + wgi, 128);
        if (warp == 0 && elect()) {
          const uint32_t src = sb + OFF_X + w * 32768 + (qi & 1) * 16384;
          tma_red(&tm_out, q * 128, mt * 128 + w * 64, src);
          tma_red(&tm_out, q * 128 + 64, mt * 128 + w * 64, src + 8192);
          bulk_commit();
          if (qi == 3 && f < 5) {
            const uint32_t dst = sb + OFF_X + w * 32768;
            mbar_expect(bars + 8 * B_XT, 16384);
            tma_ld(dst, &tm_x64, f * 128, mt * 128 + w * 64, bars + 8 * B_XT);
            tma_ld(dst + 8192, &tm_x64, f * 128 + 64, mt * 128 + w * 64, bars + 8 * B_XT);
          }
        }
      }
      if (warp == 0) bulk_wait_read<0>();
    }
  }
}

__device__ float g_fb_xn[S_ * D_], g_fb_kv[S_ * D_], g_fb_h[S_ * F_];
__device__ __forceinline__ float bf(const __nv_bfloat16* p, size_t i) { return __bfloat162float(p[i]); }
__global__ void fb_pre(Params P) {
  const int t = blockIdx.x;
  __shared__ float red[2];
  if (threadIdx.x == 0) {
    float m = 0.f, v = 0.f;
    for (int i = 0; i < D_; i++) m += bf(P.x, t * D_ + i);
    m /= D_;
    for (int i = 0; i < D_; i++) { const float d = bf(P.x, t * D_ + i) - m; v += d * d; }
    red[0] = m; red[1] = rsqrtf(v / D_ + 1e-5f);
  }
  __syncthreads();
  for (int c = threadIdx.x; c < D_; c += blockDim.x) {
    g_fb_xn[t * D_ + c] = (bf(P.x, t * D_ + c) - red[0]) * red[1];
    float a = 0.f;
    for (int j = 0; j < 4; j++) if (t - j >= 0) a += bf(P.k, (t - j) * D_ + c) * bf(P.shift, c * 4 + j);
    g_fb_kv[t * D_ + c] = bf_round(bf_round(a) * bf(P.v, t * D_ + c));
  }
  __syncthreads();
  for (int n = threadIdx.x; n < F_; n += blockDim.x) {
    float a = bf(P.b1, n);
    for (int k = 0; k < D_; k++) a += g_fb_xn[t * D_ + k] * bf(P.w1, (size_t)k * F_ + n);
    g_fb_h[t * F_ + n] = 0.5f * a * (1.f + tanhf(0.7978845608f * (a + 0.044715f * a * a * a)));
  }
}
__global__ void fb_post(Params P, const __nv_bfloat16* w2) {
  const int t = blockIdx.x;
  for (int c = threadIdx.x; c < D_; c += blockDim.x) {
    float y = g_fb_kv[t * D_ + c] * bf(P.dv, c), a = bf(P.b2, c);
    for (int j = 0; j <= t; j++) y += g_fb_kv[(t - j) * D_ + c] * bf(P.h, (size_t)c * S_ + j);
    for (int k = 0; k < F_; k++) a += g_fb_h[t * F_ + k] * bf(w2, (size_t)k * D_ + c);
    P.out[t * D_ + c] = __float2bfloat16(bf(P.x, t * D_ + c) + g_fb_xn[t * D_ + c] * y + a);
  }
}

typedef CUresult (*EncodeFn)(CUtensorMap*, CUtensorMapDataType, cuuint32_t, void*, const cuuint64_t*, const cuuint64_t*, const cuuint32_t*,
                             const cuuint32_t*, CUtensorMapInterleave, CUtensorMapSwizzle, CUtensorMapL2promotion, CUtensorMapFloatOOBfill);

CUtensorMap make_map(EncodeFn enc, const void* p, uint64_t d0, uint64_t d1, uint32_t b0, uint32_t b1) {
  CUtensorMap m;
  cuuint64_t gd[2] = {d0, d1}, gs[1] = {d0 * 2};
  cuuint32_t bx[2] = {b0, b1}, es[2] = {1, 1};
  enc(&m, CU_TENSOR_MAP_DATA_TYPE_BFLOAT16, 2, const_cast<void*>(p), gd, gs, bx, es, CU_TENSOR_MAP_INTERLEAVE_NONE,
      CU_TENSOR_MAP_SWIZZLE_128B, XPROMO, CU_TENSOR_MAP_FLOAT_OOB_FILL_NONE);
  return m;
}

CUtensorMap make_map3(EncodeFn enc, const void* p, uint64_t cols, uint64_t rows, uint32_t brows, uint32_t bgroups) {
  CUtensorMap m;
  cuuint64_t gd[3] = {64, rows, cols / 64}, gs[2] = {cols * 2, 128};
  cuuint32_t bx[3] = {64, brows, bgroups}, es[3] = {1, 1, 1};
  enc(&m, CU_TENSOR_MAP_DATA_TYPE_BFLOAT16, 3, const_cast<void*>(p), gd, gs, bx, es, CU_TENSOR_MAP_INTERLEAVE_NONE,
      CU_TENSOR_MAP_SWIZZLE_128B, CU_TENSOR_MAP_L2_PROMOTION_L2_256B, CU_TENSOR_MAP_FLOAT_OOB_FILL_NONE);
  return m;
}

CUtensorMap make_map8(EncodeFn enc, const void* p) {
  CUtensorMap m;
  cuuint64_t gd[3] = {D_, S_ / 8, 8}, gs[2] = {8 * D_ * 2, D_ * 2};
  cuuint32_t bx[3] = {8, 128, 8}, es[3] = {1, 1, 1};
  enc(&m, CU_TENSOR_MAP_DATA_TYPE_BFLOAT16, 3, const_cast<void*>(p), gd, gs, bx, es, CU_TENSOR_MAP_INTERLEAVE_NONE,
      CU_TENSOR_MAP_SWIZZLE_NONE, SLAB_PROMO, CU_TENSOR_MAP_FLOAT_OOB_FILL_NONE);
  return m;
}

CUtensorMap make_map_ur(EncodeFn enc, void* p) {
  CUtensorMap m;
  cuuint64_t gd[3] = {S_, D_ / 4, 4}, gs[2] = {4 * S_ * 2, S_ * 2};
  cuuint32_t bx[3] = {16, 16, 4}, es[3] = {1, 1, 1};
  enc(&m, CU_TENSOR_MAP_DATA_TYPE_BFLOAT16, 3, p, gd, gs, bx, es, CU_TENSOR_MAP_INTERLEAVE_NONE,
      CU_TENSOR_MAP_SWIZZLE_NONE, CU_TENSOR_MAP_L2_PROMOTION_NONE, CU_TENSOR_MAP_FLOAT_OOB_FILL_NONE);
  return m;
}

}

extern "C" void kernel_launch(void* const* d_in, const int* in_sizes, int n_in, void* d_out, int out_size) {
  (void)in_sizes; (void)n_in; (void)out_size;
  static EncodeFn enc = nullptr;
  static void* scr = nullptr;
  static bool resident = false;
  if (!enc) {
    void* fn = nullptr;
    cudaDriverEntryPointQueryResult q;
    cudaGetDriverEntryPoint("cuTensorMapEncodeTiled", &fn, cudaEnableDefault, &q);
    enc = (EncodeFn)fn;
    cudaGetSymbolAddress(&scr, g_scr);
    cudaFuncSetAttribute(fused_kernel, cudaFuncAttributeMaxDynamicSharedMemorySize, SMEM_BYTES);
    cudaLaunchConfig_t cfg = {};
    cfg.gridDim = dim3(NCTA); cfg.blockDim = dim3(NTHR); cfg.dynamicSmemBytes = SMEM_BYTES;
    cudaLaunchAttribute at;
    at.id = cudaLaunchAttributeClusterDimension; at.val.clusterDim.x = 2; at.val.clusterDim.y = 1; at.val.clusterDim.z = 1;
    cfg.attrs = &at; cfg.numAttrs = 1;
    int ncl = 0;
    resident = cudaOccupancyMaxActiveClusters(&ncl, fused_kernel, &cfg) == cudaSuccess && ncl >= NCTA / 2;
    (void)cudaGetLastError();
  }
  Params P;
  P.x = (const __nv_bfloat16*)d_in[0]; P.k = (const __nv_bfloat16*)d_in[1]; P.v = (const __nv_bfloat16*)d_in[2];
  P.shift = (const __nv_bfloat16*)d_in[3]; P.h = (const __nv_bfloat16*)d_in[4]; P.dv = (const __nv_bfloat16*)d_in[5];
  P.w1 = (const __nv_bfloat16*)d_in[7]; P.b1 = (const __nv_bfloat16*)d_in[8]; P.b2 = (const __nv_bfloat16*)d_in[10];
  P.out = (__nv_bfloat16*)d_out;
  P.s = (Scratch*)scr;
  if (!resident) {
    fb_pre<<<S_, 256>>>(P);
    fb_post<<<S_, 128>>>(P, (const __nv_bfloat16*)d_in[9]);
    return;
  }
  const CUtensorMap tm_x = make_map(enc, d_in[0], D_, S_, 64, 128), tm_x64 = make_map(enc, d_in[0], D_, S_, 64, 64);
  const CUtensorMap tm_w1 = make_map3(enc, d_in[7], F_, D_, 64, 2), tm_w2 = make_map3(enc, d_in[9], D_, F_, 128, 1);
  const CUtensorMap tm_out = make_map(enc, d_out, D_, S_, 64, 64), tm_yt = make_map(enc, P.s->yt, S_, D_, 64, 128);
  const CUtensorMap tm_k8 = make_map8(enc, d_in[1]), tm_v8 = make_map8(enc, d_in[2]);
  const CUtensorMap tm_ur = make_map_ur(enc, P.s->ur);
  fused_kernel<<<NCTA, NTHR, SMEM_BYTES>>>(P, tm_x, tm_x64, tm_w1, tm_w2, tm_out, tm_yt, tm_k8, tm_v8, tm_ur);
}
```

```cpp
#include <cuda_runtime.h>
#include <cuda_bf16.h>
#include <cuda.h>
#include <stdint.h>

namespace {

constexpr int S_ = 2048, D_ = 640, F_ = 1536;
constexpr int NCTA = 132, NTHR = 384;
#define SLAB_PROMO CU_TENSOR_MAP_L2_PROMOTION_L2_128B
#define J3_GATE 0
#define CSTAG 400
#define W2PF 3
#define MPOLL 0
#define EXTV 8
#define XPROMO CU_TENSOR_MAP_L2_PROMOTION_L2_256B
#define FIRST_GATE 3
constexpr int CONV_CL0 = 4, CONV_NCL = 18;

constexpr int C_KV = 0, C_Y = 10, C_INIT = 15, C_EPOCH = 16, C_NUM = 17;
struct Scratch {
  unsigned cnt[64 * 32];
  float4 stats[S_];
  float4 cs[2 * 4 * 6 * 96];
  __nv_bfloat16 ur[D_ * S_];
  __nv_bfloat16 yt[D_ * S_];
};
__device__ __align__(1024) Scratch g_scr;
extern __shared__ __align__(1024) uint8_t smem_raw[];
#define SMB ((uint32_t)__cvta_generic_to_shared(smem_raw))

constexpr int OFF_X = 0;
constexpr int OFF_W = 65536;
constexpr int OFF_C = OFF_W + 8 * 16384;
constexpr int ST_U = 0, ST_H0 = 4480, ST_H1 = 4480 + 4224 + 64, ST_BYTES = 13056;
constexpr int CA_MLP = 16384 + 4096 + ST_BYTES;
constexpr int CV_X = 0, CV_Y = 49152, CV_ST = 65536, CV_LN = CV_ST + 6 * ST_BYTES, LN_BYTES = 25600, CV_UX = CV_LN + 3 * LN_BYTES;
constexpr int OFF_STAT = OFF_C + CA_MLP;
constexpr int OFF_BAR = OFF_STAT + 1024;
constexpr int SMEM_BYTES = OFF_BAR + 320 + 256;
enum { B_WF = 0, B_WE = 4, B_BEXT = 8, B_U = 9, B_Y = 15, B_XT = 16, B_INIT = 17, B_NUM = 18, B_KV = B_WF, B_LN = B_WF + 2 };
static_assert(CV_UX + 2 * ST_H0 <= OFF_STAT, "smem");

__device__ __forceinline__ uint32_t smem_u32(const void* p) { return (uint32_t)__cvta_generic_to_shared(p); }
__device__ __forceinline__ void mbar_init(uint32_t b, int c) { asm volatile("mbarrier.init.shared::cta.b64 [%0], %1;" :: "r"(b), "r"(c)); }
__device__ __forceinline__ void mbar_expect(uint32_t b, uint32_t bytes) { asm volatile("mbarrier.arrive.expect_tx.shared::cta.b64 _, [%0], %1;" :: "r"(b), "r"(bytes) : "memory"); }
__device__ __forceinline__ void mbar_arrive(uint32_t b) { asm volatile("mbarrier.arrive.shared::cta.b64 _, [%0];" :: "r"(b) : "memory"); }
__device__ __forceinline__ void mbar_arrive_cl(uint32_t b) { asm volatile("mbarrier.arrive.shared::cluster.b64 _, [%0];" :: "r"(b) : "memory"); }
__device__ __forceinline__ void mbar_wait(uint32_t b, uint32_t ph) {
  asm volatile("{\n.reg .pred p;\n.reg .u32 n;\nmov.u32 n, 0;\nWL:\nmbarrier.try_wait.parity.shared::cta.b64 p, [%0], %1;\n@p bra WD;\n"
               "add.u32 n, n, 1;\nsetp.lt.u32 p, n, 1000000;\n@p bra WL;\nWD:\n}\n" :: "r"(b), "r"(ph) : "memory");
}
__device__ __forceinline__ uint32_t mapa(uint32_t a, uint32_t r) { uint32_t o; asm("mapa.shared::cluster.u32 %0, %1, %2;" : "=r"(o) : "r"(a), "r"(r)); return o; }
__device__ __forceinline__ void flag_wait(const unsigned* cnt, int c, unsigned target) {
  asm volatile("{\n.reg .pred p;\n.reg .u32 n, v;\nmov.u32 n, 0;\nFL:\nld.relaxed.gpu.global.u32 v, [%0];\nsub.u32 v, v, %1;\nsetp.ge.s32 p, v, 0;\n@p bra FD;\n"
               "nanosleep.u32 20;\nadd.u32 n, n, 1;\nsetp.lt.u32 p, n, 2000000;\n@p bra FL;\nFD:\n}\n" :: "l"(cnt + c * 32), "r"(target) : "memory");
}
__device__ __forceinline__ bool elect() { uint32_t r; asm volatile("{.reg .pred p; elect.sync _|p, 0xffffffff; selp.u32 %0, 1, 0, p;}" : "=r"(r)); return r; }
__device__ __forceinline__ void flag_add(unsigned* cnt, int c) { asm volatile("red.release.gpu.global.add.u32 [%0], 1;" :: "l"(cnt + c * 32) : "memory"); }
__device__ __forceinline__ void fence_async() { asm volatile("fence.proxy.async.global;" ::: "memory"); }
__device__ __forceinline__ void fence_gpu() { asm volatile("fence.acq_rel.gpu;" ::: "memory"); }
__device__ __forceinline__ void flag_add_relaxed(unsigned* cnt, int c) { asm volatile("red.relaxed.gpu.global.add.u32 [%0], 1;" :: "l"(cnt + c * 32) : "memory"); }
__device__ __forceinline__ bool mbar_test(uint32_t b, uint32_t ph) {
  uint32_t ok; asm volatile("{.reg .pred p; mbarrier.test_wait.parity.shared::cta.b64 p, [%1], %2; selp.u32 %0, 1, 0, p;}" : "=r"(ok) : "r"(b), "r"(ph) : "memory"); return ok;
}
__device__ __forceinline__ void red4f(float* p, float a, float b, float c, float d) { asm volatile("red.relaxed.gpu.global.add.v4.f32 [%0], {%1,%2,%3,%4};" :: "l"(p), "f"(a), "f"(b), "f"(c), "f"(d) : "memory"); }
__device__ __forceinline__ void tma_prefetch3(const CUtensorMap* m, int y, int z) { asm volatile("cp.async.bulk.prefetch.tensor.3d.L2.global.tile [%0, {0, %1, %2}];" :: "l"(m), "r"(y), "r"(z) : "memory"); }
__device__ __forceinline__ void map_prefetch(const CUtensorMap* m) { asm volatile("prefetch.tensormap [%0];" :: "l"(m) : "memory"); }
__device__ __forceinline__ void fence_async_smem() { asm volatile("fence.proxy.async.shared::cta;" ::: "memory"); }
__device__ __forceinline__ void bar_sync(int id, int n) { asm volatile("bar.sync %0, %1;" :: "r"(id), "r"(n) : "memory"); }
__device__ __forceinline__ void bar_arrive(int id, int n) { asm volatile("bar.arrive %0, %1;" :: "r"(id), "r"(n) : "memory"); }
__device__ __forceinline__ void bulk_g2s(uint32_t dst, const void* src, uint32_t bytes, uint32_t bar) {
  asm volatile("cp.async.bulk.shared::cluster.global.mbarrier::complete_tx::bytes [%0], [%1], %2, [%3];" :: "r"(dst), "l"(src), "r"(bytes), "r"(bar) : "memory");
}
__device__ __forceinline__ void bulk_s2g(void* dst, uint32_t src, uint32_t bytes) {
  asm volatile("cp.async.bulk.global.shared::cta.bulk_group [%0], [%1], %2;" :: "l"(dst), "r"(src), "r"(bytes) : "memory");
}
__device__ __forceinline__ void tma_ld(uint32_t dst, const CUtensorMap* m, int x, int y, uint32_t bar) {
  asm volatile("cp.async.bulk.tensor.2d.shared::cluster.global.mbarrier::complete_tx::bytes [%0], [%1, {%3, %4}], [%2];"
               :: "r"(dst), "l"(m), "r"(bar), "r"(x), "r"(y) : "memory");
}
__device__ __forceinline__ void tma_ld3(uint32_t dst, const CUtensorMap* m, int y, int z, uint32_t bar) {
  asm volatile("cp.async.bulk.tensor.3d.shared::cluster.global.mbarrier::complete_tx::bytes [%0], [%1, {0, %3, %4}], [%2];"
               :: "r"(dst), "l"(m), "r"(bar), "r"(y), "r"(z) : "memory");
}
__device__ __forceinline__ void tma_ld3_mc(uint32_t dst, const CUtensorMap* m, int y, int z, uint32_t bar) {
  asm volatile("cp.async.bulk.tensor.3d.shared::cluster.global.mbarrier::complete_tx::bytes.multicast::cluster [%0], [%1, {0, %3, %4}], [%2], %5;"
               :: "r"(dst), "l"(m), "r"(bar), "r"(y), "r"(z), "h"((uint16_t)3) : "memory");
}
__device__ __forceinline__ void tma_ld3x(uint32_t dst, const CUtensorMap* m, int x, int y, uint32_t bar) {
  asm volatile("cp.async.bulk.tensor.3d.shared::cluster.global.mbarrier::complete_tx::bytes [%0], [%1, {%3, %4, 0}], [%2];"
               :: "r"(dst), "l"(m), "r"(bar), "r"(x), "r"(y) : "memory");
}
__device__ __forceinline__ void tma_st3(const CUtensorMap* m, int x, int y, uint32_t src) {
  asm volatile("cp.async.bulk.tensor.3d.global.shared::cta.tile.bulk_group [%0, {%2, %3, 0}], [%1];" :: "l"(m), "r"(src), "r"(x), "r"(y) : "memory");
}
__device__ __forceinline__ void tma_red(const CUtensorMap* m, int x, int y, uint32_t src) {
  asm volatile("cp.reduce.async.bulk.tensor.2d.global.shared::cta.add.tile.bulk_group [%0, {%2, %3}], [%1];" :: "l"(m), "r"(src), "r"(x), "r"(y) : "memory");
}
__device__ __forceinline__ void bulk_commit() { asm volatile("cp.async.bulk.commit_group;" ::: "memory"); }
template <int N> __device__ __forceinline__ void bulk_wait_read() { asm volatile("cp.async.bulk.wait_group.read %0;" :: "n"(N) : "memory"); }
template <int N> __device__ __forceinline__ void bulk_wait() { asm volatile("cp.async.bulk.wait_group %0;" :: "n"(N) : "memory"); }
__device__ __forceinline__ void wg_fence() { asm volatile("wgmma.fence.sync.aligned;" ::: "memory"); }
__device__ __forceinline__ void wg_commit() { asm volatile("wgmma.commit_group.sync.aligned;" ::: "memory"); }
template <int N> __device__ __forceinline__ void wg_wait() { asm volatile("wgmma.wait_group.sync.aligned %0;" :: "n"(N) : "memory"); }
__device__ __forceinline__ uint32_t lds32(uint32_t a) { uint32_t v; asm volatile("ld.shared.u32 %0, [%1];" : "=r"(v) : "r"(a)); return v; }
__device__ __forceinline__ void sts32(uint32_t a, uint32_t v) { asm volatile("st.shared.u32 [%0], %1;" :: "r"(a), "r"(v) : "memory"); }
__device__ __forceinline__ void sts32p(uint32_t a, uint32_t v, bool p) { asm volatile("{.reg .pred q; setp.ne.b32 q, %2, 0; @q st.shared.u32 [%0], %1;}" :: "r"(a), "r"(v), "r"((int)p) : "memory"); }
__device__ __forceinline__ void sts128(uint32_t a, uint32_t x, uint32_t y, uint32_t z, uint32_t w) { asm volatile("st.shared.v4.u32 [%0], {%1,%2,%3,%4};" :: "r"(a), "r"(x), "r"(y), "r"(z), "r"(w) : "memory"); }
__device__ __forceinline__ uint4 lds128(uint32_t a) { uint4 v; asm volatile("ld.shared.v4.u32 {%0,%1,%2,%3}, [%4];" : "=r"(v.x), "=r"(v.y), "=r"(v.z), "=r"(v.w) : "r"(a) : "memory"); return v; }
__device__ __forceinline__ uint2 lds64(uint32_t a) { uint2 v; asm volatile("ld.shared.v2.u32 {%0,%1}, [%2];" : "=r"(v.x), "=r"(v.y) : "r"(a) : "memory"); return v; }
__device__ __forceinline__ void st128(void* p, uint32_t x, uint32_t y, uint32_t z, uint32_t w) { asm volatile("st.v4.u32 [%0], {%1,%2,%3,%4};" :: "l"(p), "r"(x), "r"(y), "r"(z), "r"(w) : "memory"); }
__device__ __forceinline__ uint4 lds128_ro(uint32_t a) { uint4 v; asm("ld.shared.v4.u32 {%0,%1,%2,%3}, [%4];" : "=r"(v.x), "=r"(v.y), "=r"(v.z), "=r"(v.w) : "r"(a)); return v; }
__device__ __forceinline__ float2 lds64f(uint32_t a) { float2 v; asm volatile("ld.shared.v2.f32 {%0,%1}, [%2];" : "=f"(v.x), "=f"(v.y) : "r"(a) : "memory"); return v; }
__device__ __forceinline__ float4 lds128f(uint32_t a) { float4 v; asm volatile("ld.shared.v4.f32 {%0,%1,%2,%3}, [%4];" : "=f"(v.x), "=f"(v.y), "=f"(v.z), "=f"(v.w) : "r"(a)); return v; }
__device__ __forceinline__ void stsm4(uint32_t a, uint32_t x, uint32_t y, uint32_t z, uint32_t w) { asm volatile("stmatrix.sync.aligned.m8n8.x4.shared.b16 [%0], {%1,%2,%3,%4};" :: "r"(a), "r"(x), "r"(y), "r"(z), "r"(w) : "memory"); }
__device__ __forceinline__ void stsm4t(uint32_t a, uint32_t x, uint32_t y, uint32_t z, uint32_t w) { asm volatile("stmatrix.sync.aligned.m8n8.x4.trans.shared.b16 [%0], {%1,%2,%3,%4};" :: "r"(a), "r"(x), "r"(y), "r"(z), "r"(w) : "memory"); }
__device__ __forceinline__ void ldsm4(uint32_t a, uint32_t* r) { asm volatile("ldmatrix.sync.aligned.m8n8.x4.shared.b16 {%0,%1,%2,%3}, [%4];" : "=r"(r[0]), "=r"(r[1]), "=r"(r[2]), "=r"(r[3]) : "r"(a) : "memory"); }
__device__ __forceinline__ void ldsm4t(uint32_t a, uint32_t* r) { asm volatile("ldmatrix.sync.aligned.m8n8.x4.trans.shared.b16 {%0,%1,%2,%3}, [%4];" : "=r"(r[0]), "=r"(r[1]), "=r"(r[2]), "=r"(r[3]) : "r"(a) : "memory"); }
__device__ __forceinline__ uint32_t pack2(float lo, float hi) { uint32_t r; asm("cvt.rn.bf16x2.f32 %0, %1, %2;" : "=r"(r) : "f"(hi), "f"(lo)); return r; }
__device__ __forceinline__ float bf_lo(uint32_t v) { return __uint_as_float(v << 16); }
__device__ __forceinline__ float bf_hi(uint32_t v) { return __uint_as_float(v & 0xffff0000u); }
__device__ __forceinline__ float bf_round(float v) { return bf_lo(pack2(v, 0.f)); }
__device__ __forceinline__ uint32_t hadd2(uint32_t a, uint32_t b) { uint32_t r; asm("add.rn.bf16x2 %0, %1, %2;" : "=r"(r) : "r"(a), "r"(b)); return r; }
__device__ __forceinline__ uint32_t hsub2(uint32_t a, uint32_t b) { uint32_t r; asm("sub.rn.bf16x2 %0, %1, %2;" : "=r"(r) : "r"(a), "r"(b)); return r; }
__device__ __forceinline__ uint32_t hmul2(uint32_t a, uint32_t b) { uint32_t r; asm("mul.rn.bf16x2 %0, %1, %2;" : "=r"(r) : "r"(a), "r"(b)); return r; }
__device__ __forceinline__ uint32_t hfma2(uint32_t a, uint32_t b, uint32_t c) { uint32_t r; asm("fma.rn.bf16x2 %0, %1, %2, %3;" : "=r"(r) : "r"(a), "r"(b), "r"(c)); return r; }
__device__ __forceinline__ float tanh_fast(float x) { float r; asm("tanh.approx.f32 %0, %1;" : "=f"(r) : "f"(x)); return r; }
__device__ __forceinline__ float rcp_fast(float x) { float r; asm("rcp.approx.ftz.f32 %0, %1;" : "=f"(r) : "f"(x)); return r; }
__device__ __forceinline__ float rsqrt_fast(float x) { float r; asm("rsqrt.approx.ftz.f32 %0, %1;" : "=f"(r) : "f"(x)); return r; }
__device__ __forceinline__ uint4 ldg128(const void* p) { uint4 v; asm volatile("ld.global.nc.L1::no_allocate.v4.u32 {%0,%1,%2,%3}, [%4];" : "=r"(v.x), "=r"(v.y), "=r"(v.z), "=r"(v.w) : "l"(p)); return v; }
__device__ __forceinline__ uint2 ldg64(const void* p) { uint2 v; asm volatile("ld.global.nc.L1::no_allocate.v2.u32 {%0,%1}, [%2];" : "=r"(v.x), "=r"(v.y) : "l"(p)); return v; }
__device__ __forceinline__ uint32_t ldg32(const void* p) { uint32_t v; asm volatile("ld.global.nc.u32 %0, [%1];" : "=r"(v) : "l"(p)); return v; }
__device__ __forceinline__ float4 ldcg128f(const void* p) { float4 v; asm volatile("ld.global.cg.v4.f32 {%0,%1,%2,%3}, [%4];" : "=f"(v.x), "=f"(v.y), "=f"(v.z), "=f"(v.w) : "l"(p) : "memory"); return v; }
__device__ __forceinline__ float4 ld_relaxed4(const void* p) { float4 v; asm volatile("ld.relaxed.gpu.global.v4.f32 {%0,%1,%2,%3}, [%4];" : "=f"(v.x), "=f"(v.y), "=f"(v.z), "=f"(v.w) : "l"(p) : "memory"); return v; }
__device__ __forceinline__ float2 ldcg64f(const void* p) { float2 v; asm volatile("ld.global.cg.v2.f32 {%0,%1}, [%2];" : "=f"(v.x), "=f"(v.y) : "l"(p) : "memory"); return v; }
__device__ __forceinline__ void stg128(void* p, uint32_t x, uint32_t y, uint32_t z, uint32_t w) { asm volatile("st.global.v4.u32 [%0], {%1,%2,%3,%4};" :: "l"(p), "r"(x), "r"(y), "r"(z), "r"(w) : "memory"); }
__device__ __forceinline__ void cluster_arrive() { asm volatile("barrier.cluster.arrive.relaxed.aligned;" ::: "memory"); }
__device__ __forceinline__ void cluster_wait() { asm volatile("barrier.cluster.wait.acquire.aligned;" ::: "memory"); }

__device__ __forceinline__ void wg_ss256(float (&d)[128], uint32_t alo, uint32_t blo, uint32_t sc) {
  asm volatile("{\n.reg .pred p;\n.reg .b64 da, db;\nmov.b64 da, {%128, 0x40000040};\nmov.b64 db, {%129, 0x40000040};\nsetp.ne.b32 p, %130, 0;\n"
    "wgmma.mma_async.sync.aligned.m64n256k16.f32.bf16.bf16 {%0, %1, %2, %3, %4, %5, %6, %7, %8, %9, %10, %11, %12, %13, %14, %15, %16, %17, %18, %19, %20, %21, %22, %23, %24, %25, %26, %27, %28, %29, %30, %31, %32, %33, %34, %35, %36, %37, %38, %39, %40, %41, %42, %43, %44, %45, %46, %47, %48, %49, %50, %51, %52, %53, %54, %55, %56, %57, %58, %59, %60, %61, %62, %63, %64, %65, %66, %67, %68, %69, %70, %71, %72, %73, %74, %75, %76, %77, %78, %79, %80, %81, %82, %83, %84, %85, %86, %87, %88, %89, %90, %91, %92, %93, %94, %95, %96, %97, %98, %99, %100, %101, %102, %103, %104, %105, %106, %107, %108, %109, %110, %111, %112, %113, %114, %115, %116, %117, %118, %119, %120, %121, %122, %123, %124, %125, %126, %127}, da, db, p, 1, 1, 0, 1;\n}\n"
    : "+f"(d[0]), "+f"(d[1]), "+f"(d[2]), "+f"(d[3]), "+f"(d[4]), "+f"(d[5]), "+f"(d[6]), "+f"(d[7]), "+f"(d[8]), "+f"(d[9]), "+f"(d[10]), "+f"(d[11]), "+f"(d[12]), "+f"(d[13]), "+f"(d[14]), "+f"(d[15]), "+f"(d[16]), "+f"(d[17]), "+f"(d[18]), "+f"(d[19]), "+f"(d[20]), "+f"(d[21]), "+f"(d[22]), "+f"(d[23]), "+f"(d[24]), "+f"(d[25]), "+f"(d[26]), "+f"(d[27]), "+f"(d[28]), "+f"(d[29]), "+f"(d[30]), "+f"(d[31]), "+f"(d[32]), "+f"(d[33]), "+f"(d[34]), "+f"(d[35]), "+f"(d[36]), "+f"(d[37]), "+f"(d[38]), "+f"(d[39]), "+f"(d[40]), "+f"(d[41]), "+f"(d[42]), "+f"(d[43]), "+f"(d[44]), "+f"(d[45]), "+f"(d[46]), "+f"(d[47]), "+f"(d[48]), "+f"(d[49]), "+f"(d[50]), "+f"(d[51]), "+f"(d[52]), "+f"(d[53]), "+f"(d[54]), "+f"(d[55]), "+f"(d[56]), "+f"(d[57]), "+f"(d[58]), "+f"(d[59]), "+f"(d[60]), "+f"(d[61]), "+f"(d[62]), "+f"(d[63]), "+f"(d[64]), "+f"(d[65]), "+f"(d[66]), "+f"(d[67]), "+f"(d[68]), "+f"(d[69]), "+f"(d[70]), "+f"(d[71]), "+f"(d[72]), "+f"(d[73]), "+f"(d[74]), "+f"(d[75]), "+f"(d[76]), "+f"(d[77]), "+f"(d[78]), "+f"(d[79]), "+f"(d[80]), "+f"(d[81]), "+f"(d[82]), "+f"(d[83]), "+f"(d[84]), "+f"(d[85]), "+f"(d[86]), "+f"(d[87]), "+f"(d[88]), "+f"(d[89]), "+f"(d[90]), "+f"(d[91]), "+f"(d[92]), "+f"(d[93]), "+f"(d[94]), "+f"(d[95]), "+f"(d[96]), "+f"(d[97]), "+f"(d[98]), "+f"(d[99]), "+f"(d[100]), "+f"(d[101]), "+f"(d[102]), "+f"(d[103]), "+f"(d[104]), "+f"(d[105]), "+f"(d[106]), "+f"(d[107]), "+f"(d[108]), "+f"(d[109]), "+f"(d[110]), "+f"(d[111]), "+f"(d[112]), "+f"(d[113]), "+f"(d[114]), "+f"(d[115]), "+f"(d[116]), "+f"(d[117]), "+f"(d[118]), "+f"(d[119]), "+f"(d[120]), "+f"(d[121]), "+f"(d[122]), "+f"(d[123]), "+f"(d[124]), "+f"(d[125]), "+f"(d[126]), "+f"(d[127]) : "r"(alo), "r"(blo), "r"(sc));
}
__device__ __forceinline__ void wg_rs256(float (&d)[128], uint32_t a0, uint32_t a1, uint32_t a2, uint32_t a3, uint32_t blo, uint32_t sc) {
  asm volatile("{\n.reg .pred p;\n.reg .b64 db;\nmov.b64 db, {%132, 0x40000040};\nsetp.ne.b32 p, %133, 0;\n"
    "wgmma.mma_async.sync.aligned.m64n256k16.f32.bf16.bf16 {%0, %1, %2, %3, %4, %5, %6, %7, %8, %9, %10, %11, %12, %13, %14, %15, %16, %17, %18, %19, %20, %21, %22, %23, %24, %25, %26, %27, %28, %29, %30, %31, %32, %33, %34, %35, %36, %37, %38, %39, %40, %41, %42, %43, %44, %45, %46, %47, %48, %49, %50, %51, %52, %53, %54, %55, %56, %57, %58, %59, %60, %61, %62, %63, %64, %65, %66, %67, %68, %69, %70, %71, %72, %73, %74, %75, %76, %77, %78, %79, %80, %81, %82, %83, %84, %85, %86, %87, %88, %89, %90, %91, %92, %93, %94, %95, %96, %97, %98, %99, %100, %101, %102, %103, %104, %105, %106, %107, %108, %109, %110, %111, %112, %113, %114, %115, %116, %117, %118, %119, %120, %121, %122, %123, %124, %125, %126, %127}, {%128,%129,%130,%131}, db, p, 1, 1, 1;\n}\n"
    : "+f"(d[0]), "+f"(d[1]), "+f"(d[2]), "+f"(d[3]), "+f"(d[4]), "+f"(d[5]), "+f"(d[6]), "+f"(d[7]), "+f"(d[8]), "+f"(d[9]), "+f"(d[10]), "+f"(d[11]), "+f"(d[12]), "+f"(d[13]), "+f"(d[14]), "+f"(d[15]), "+f"(d[16]), "+f"(d[17]), "+f"(d[18]), "+f"(d[19]), "+f"(d[20]), "+f"(d[21]), "+f"(d[22]), "+f"(d[23]), "+f"(d[24]), "+f"(d[25]), "+f"(d[26]), "+f"(d[27]), "+f"(d[28]), "+f"(d[29]), "+f"(d[30]), "+f"(d[31]), "+f"(d[32]), "+f"(d[33]), "+f"(d[34]), "+f"(d[35]), "+f"(d[36]), "+f"(d[37]), "+f"(d[38]), "+f"(d[39]), "+f"(d[40]), "+f"(d[41]), "+f"(d[42]), "+f"(d[43]), "+f"(d[44]), "+f"(d[45]), "+f"(d[46]), "+f"(d[47]), "+f"(d[48]), "+f"(d[49]), "+f"(d[50]), "+f"(d[51]), "+f"(d[52]), "+f"(d[53]), "+f"(d[54]), "+f"(d[55]), "+f"(d[56]), "+f"(d[57]), "+f"(d[58]), "+f"(d[59]), "+f"(d[60]), "+f"(d[61]), "+f"(d[62]), "+f"(d[63]), "+f"(d[64]), "+f"(d[65]), "+f"(d[66]), "+f"(d[67]), "+f"(d[68]), "+f"(d[69]), "+f"(d[70]), "+f"(d[71]), "+f"(d[72]), "+f"(d[73]), "+f"(d[74]), "+f"(d[75]), "+f"(d[76]), "+f"(d[77]), "+f"(d[78]), "+f"(d[79]), "+f"(d[80]), "+f"(d[81]), "+f"(d[82]), "+f"(d[83]), "+f"(d[84]), "+f"(d[85]), "+f"(d[86]), "+f"(d[87]), "+f"(d[88]), "+f"(d[89]), "+f"(d[90]), "+f"(d[91]), "+f"(d[92]), "+f"(d[93]), "+f"(d[94]), "+f"(d[95]), "+f"(d[96]), "+f"(d[97]), "+f"(d[98]), "+f"(d[99]), "+f"(d[100]), "+f"(d[101]), "+f"(d[102]), "+f"(d[103]), "+f"(d[104]), "+f"(d[105]), "+f"(d[106]), "+f"(d[107]), "+f"(d[108]), "+f"(d[109]), "+f"(d[110]), "+f"(d[111]), "+f"(d[112]), "+f"(d[113]), "+f"(d[114]), "+f"(d[115]), "+f"(d[116]), "+f"(d[117]), "+f"(d[118]), "+f"(d[119]), "+f"(d[120]), "+f"(d[121]), "+f"(d[122]), "+f"(d[123]), "+f"(d[124]), "+f"(d[125]), "+f"(d[126]), "+f"(d[127]) : "r"(a0), "r"(a1), "r"(a2), "r"(a3), "r"(blo), "r"(sc));
}
__device__ __forceinline__ void wg_rs256x(float (&d)[128], uint32_t a0, uint32_t a1, uint32_t blo) {
  asm volatile("{\n.reg .b64 db;\nmov.b64 db, {%131, 0x40000000};\n"
    "wgmma.mma_async.sync.aligned.m64n256k16.f32.bf16.bf16 {%0, %1, %2, %3, %4, %5, %6, %7, %8, %9, %10, %11, %12, %13, %14, %15, %16, %17, %18, %19, %20, %21, %22, %23, %24, %25, %26, %27, %28, %29, %30, %31, %32, %33, %34, %35, %36, %37, %38, %39, %40, %41, %42, %43, %44, %45, %46, %47, %48, %49, %50, %51, %52, %53, %54, %55, %56, %57, %58, %59, %60, %61, %62, %63, %64, %65, %66, %67, %68, %69, %70, %71, %72, %73, %74, %75, %76, %77, %78, %79, %80, %81, %82, %83, %84, %85, %86, %87, %88, %89, %90, %91, %92, %93, %94, %95, %96, %97, %98, %99, %100, %101, %102, %103, %104, %105, %106, %107, %108, %109, %110, %111, %112, %113, %114, %115, %116, %117, %118, %119, %120, %121, %122, %123, %124, %125, %126, %127}, {%128,%129,%130,%130}, db, 1, 1, 1, 1;\n}\n"
    : "+f"(d[0]), "+f"(d[1]), "+f"(d[2]), "+f"(d[3]), "+f"(d[4]), "+f"(d[5]), "+f"(d[6]), "+f"(d[7]), "+f"(d[8]), "+f"(d[9]), "+f"(d[10]), "+f"(d[11]), "+f"(d[12]), "+f"(d[13]), "+f"(d[14]), "+f"(d[15]), "+f"(d[16]), "+f"(d[17]), "+f"(d[18]), "+f"(d[19]), "+f"(d[20]), "+f"(d[21]), "+f"(d[22]), "+f"(d[23]), "+f"(d[24]), "+f"(d[25]), "+f"(d[26]), "+f"(d[27]), "+f"(d[28]), "+f"(d[29]), "+f"(d[30]), "+f"(d[31]), "+f"(d[32]), "+f"(d[33]), "+f"(d[34]), "+f"(d[35]), "+f"(d[36]), "+f"(d[37]), "+f"(d[38]), "+f"(d[39]), "+f"(d[40]), "+f"(d[41]), "+f"(d[42]), "+f"(d[43]), "+f"(d[44]), "+f"(d[45]), "+f"(d[46]), "+f"(d[47]), "+f"(d[48]), "+f"(d[49]), "+f"(d[50]), "+f"(d[51]), "+f"(d[52]), "+f"(d[53]), "+f"(d[54]), "+f"(d[55]), "+f"(d[56]), "+f"(d[57]), "+f"(d[58]), "+f"(d[59]), "+f"(d[60]), "+f"(d[61]), "+f"(d[62]), "+f"(d[63]), "+f"(d[64]), "+f"(d[65]), "+f"(d[66]), "+f"(d[67]), "+f"(d[68]), "+f"(d[69]), "+f"(d[70]), "+f"(d[71]), "+f"(d[72]), "+f"(d[73]), "+f"(d[74]), "+f"(d[75]), "+f"(d[76]), "+f"(d[77]), "+f"(d[78]), "+f"(d[79]), "+f"(d[80]), "+f"(d[81]), "+f"(d[82]), "+f"(d[83]), "+f"(d[84]), "+f"(d[85]), "+f"(d[86]), "+f"(d[87]), "+f"(d[88]), "+f"(d[89]), "+f"(d[90]), "+f"(d[91]), "+f"(d[92]), "+f"(d[93]), "+f"(d[94]), "+f"(d[95]), "+f"(d[96]), "+f"(d[97]), "+f"(d[98]), "+f"(d[99]), "+f"(d[100]), "+f"(d[101]), "+f"(d[102]), "+f"(d[103]), "+f"(d[104]), "+f"(d[105]), "+f"(d[106]), "+f"(d[107]), "+f"(d[108]), "+f"(d[109]), "+f"(d[110]), "+f"(d[111]), "+f"(d[112]), "+f"(d[113]), "+f"(d[114]), "+f"(d[115]), "+f"(d[116]), "+f"(d[117]), "+f"(d[118]), "+f"(d[119]), "+f"(d[120]), "+f"(d[121]), "+f"(d[122]), "+f"(d[123]), "+f"(d[124]), "+f"(d[125]), "+f"(d[126]), "+f"(d[127]) : "r"(a0), "r"(a1), "r"(0u), "r"(blo));
}
__device__ __forceinline__ void wg_rs128(float (&d)[64], const uint32_t* a, uint32_t blo, uint32_t sc) {
  asm volatile("{\n.reg .pred p;\n.reg .b64 db;\nmov.b64 db, {%68, 0x40000040};\nsetp.ne.b32 p, %69, 0;\n"
    "wgmma.mma_async.sync.aligned.m64n128k16.f32.bf16.bf16 {%0, %1, %2, %3, %4, %5, %6, %7, %8, %9, %10, %11, %12, %13, %14, %15, %16, %17, %18, %19, %20, %21, %22, %23, %24, %25, %26, %27, %28, %29, %30, %31, %32, %33, %34, %35, %36, %37, %38, %39, %40, %41, %42, %43, %44, %45, %46, %47, %48, %49, %50, %51, %52, %53, %54, %55, %56, %57, %58, %59, %60, %61, %62, %63}, {%64,%65,%66,%67}, db, p, 1, 1, 1;\n}\n"
    : "+f"(d[0]), "+f"(d[1]), "+f"(d[2]), "+f"(d[3]), "+f"(d[4]), "+f"(d[5]), "+f"(d[6]), "+f"(d[7]), "+f"(d[8]), "+f"(d[9]), "+f"(d[10]), "+f"(d[11]), "+f"(d[12]), "+f"(d[13]), "+f"(d[14]), "+f"(d[15]), "+f"(d[16]), "+f"(d[17]), "+f"(d[18]), "+f"(d[19]), "+f"(d[20]), "+f"(d[21]), "+f"(d[22]), "+f"(d[23]), "+f"(d[24]), "+f"(d[25]), "+f"(d[26]), "+f"(d[27]), "+f"(d[28]), "+f"(d[29]), "+f"(d[30]), "+f"(d[31]), "+f"(d[32]), "+f"(d[33]), "+f"(d[34]), "+f"(d[35]), "+f"(d[36]), "+f"(d[37]), "+f"(d[38]), "+f"(d[39]), "+f"(d[40]), "+f"(d[41]), "+f"(d[42]), "+f"(d[43]), "+f"(d[44]), "+f"(d[45]), "+f"(d[46]), "+f"(d[47]), "+f"(d[48]), "+f"(d[49]), "+f"(d[50]), "+f"(d[51]), "+f"(d[52]), "+f"(d[53]), "+f"(d[54]), "+f"(d[55]), "+f"(d[56]), "+f"(d[57]), "+f"(d[58]), "+f"(d[59]), "+f"(d[60]), "+f"(d[61]), "+f"(d[62]), "+f"(d[63]) : "r"(a[0]), "r"(a[1]), "r"(a[2]), "r"(a[3]), "r"(blo), "r"(sc));
}
template<int OFF, int SC> __device__ __forceinline__ void wg_rs32(float (&d)[64], const uint32_t* a, uint32_t blo);
template<> __device__ __forceinline__ void wg_rs32<0,0>(float (&d)[64], const uint32_t* a, uint32_t blo) {
  asm volatile("{\n.reg .pred p;\n.reg .b64 db;\nmov.b64 db, {%20, 8};\nsetp.ne.b32 p, 0, 0;\n"
    "wgmma.mma_async.sync.aligned.m64n32k16.f32.bf16.bf16 {%0, %1, %2, %3, %4, %5, %6, %7, %8, %9, %10, %11, %12, %13, %14, %15}, {%16,%17,%18,%19}, db, p, 1, 1, 0;\n}\n"
    : "+f"(d[0]), "+f"(d[1]), "+f"(d[2]), "+f"(d[3]), "+f"(d[4]), "+f"(d[5]), "+f"(d[6]), "+f"(d[7]), "+f"(d[8]), "+f"(d[9]), "+f"(d[10]), "+f"(d[11]), "+f"(d[12]), "+f"(d[13]), "+f"(d[14]), "+f"(d[15]) : "r"(a[0]), "r"(a[1]), "r"(a[2]), "r"(a[3]), "r"(blo));
}
template<> __device__ __forceinline__ void wg_rs32<0,1>(float (&d)[64], const uint32_t* a, uint32_t blo) {
  asm volatile("{\n.reg .pred p;\n.reg .b64 db;\nmov.b64 db, {%20, 8};\nsetp.ne.b32 p, 1, 0;\n"
    "wgmma.mma_async.sync.aligned.m64n32k16.f32.bf16.bf16 {%0, %1, %2, %3, %4, %5, %6, %7, %8, %9, %10, %11, %12, %13, %14, %15}, {%16,%17,%18,%19}, db, p, 1, 1, 0;\n}\n"
    : "+f"(d[0]), "+f"(d[1]), "+f"(d[2]), "+f"(d[3]), "+f"(d[4]), "+f"(d[5]), "+f"(d[6]), "+f"(d[7]), "+f"(d[8]), "+f"(d[9]), "+f"(d[10]), "+f"(d[11]), "+f"(d[12]), "+f"(d[13]), "+f"(d[14]), "+f"(d[15]) : "r"(a[0]), "r"(a[1]), "r"(a[2]), "r"(a[3]), "r"(blo));
}
template<> __device__ __forceinline__ void wg_rs32<16,0>(float (&d)[64], const uint32_t* a, uint32_t blo) {
  asm volatile("{\n.reg .pred p;\n.reg .b64 db;\nmov.b64 db, {%20, 8};\nsetp.ne.b32 p, 0, 0;\n"
    "wgmma.mma_async.sync.aligned.m64n32k16.f32.bf16.bf16 {%0, %1, %2, %3, %4, %5, %6, %7, %8, %9, %10, %11, %12, %13, %14, %15}, {%16,%17,%18,%19}, db, p, 1, 1, 0;\n}\n"
    : "+f"(d[16]), "+f"(d[17]), "+f"(d[18]), "+f"(d[19]), "+f"(d[20]), "+f"(d[21]), "+f"(d[22]), "+f"(d[23]), "+f"(d[24]), "+f"(d[25]), "+f"(d[26]), "+f"(d[27]), "+f"(d[28]), "+f"(d[29]), "+f"(d[30]), "+f"(d[31]) : "r"(a[0]), "r"(a[1]), "r"(a[2]), "r"(a[3]), "r"(blo));
}
template<> __device__ __forceinline__ void wg_rs32<16,1>(float (&d)[64], const uint32_t* a, uint32_t blo) {
  asm volatile("{\n.reg .pred p;\n.reg .b64 db;\nmov.b64 db, {%20, 8};\nsetp.ne.b32 p, 1, 0;\n"
    "wgmma.mma_async.sync.aligned.m64n32k16.f32.bf16.bf16 {%0, %1, %2, %3, %4, %5, %6, %7, %8, %9, %10, %11, %12, %13, %14, %15}, {%16,%17,%18,%19}, db, p, 1, 1, 0;\n}\n"
    : "+f"(d[16]), "+f"(d[17]), "+f"(d[18]), "+f"(d[19]), "+f"(d[20]), "+f"(d[21]), "+f"(d[22]), "+f"(d[23]), "+f"(d[24]), "+f"(d[25]), "+f"(d[26]), "+f"(d[27]), "+f"(d[28]), "+f"(d[29]), "+f"(d[30]), "+f"(d[31]) : "r"(a[0]), "r"(a[1]), "r"(a[2]), "r"(a[3]), "r"(blo));
}
template<> __device__ __forceinline__ void wg_rs32<32,0>(float (&d)[64], const uint32_t* a, uint32_t blo) {
  asm volatile("{\n.reg .pred p;\n.reg .b64 db;\nmov.b64 db, {%20, 8};\nsetp.ne.b32 p, 0, 0;\n"
    "wgmma.mma_async.sync.aligned.m64n32k16.f32.bf16.bf16 {%0, %1, %2, %3, %4, %5, %6, %7, %8, %9, %10, %11, %12, %13, %14, %15}, {%16,%17,%18,%19}, db, p, 1, 1, 0;\n}\n"
    : "+f"(d[32]), "+f"(d[33]), "+f"(d[34]), "+f"(d[35]), "+f"(d[36]), "+f"(d[37]), "+f"(d[38]), "+f"(d[39]), "+f"(d[40]), "+f"(d[41]), "+f"(d[42]), "+f"(d[43]), "+f"(d[44]), "+f"(d[45]), "+f"(d[46]), "+f"(d[47]) : "r"(a[0]), "r"(a[1]), "r"(a[2]), "r"(a[3]), "r"(blo));
}
template<> __device__ __forceinline__ void wg_rs32<32,1>(float (&d)[64], const uint32_t* a, uint32_t blo) {
  asm volatile("{\n.reg .pred p;\n.reg .b64 db;\nmov.b64 db, {%20, 8};\nsetp.ne.b32 p, 1, 0;\n"
    "wgmma.mma_async.sync.aligned.m64n32k16.f32.bf16.bf16 {%0, %1, %2, %3, %4, %5, %6, %7, %8, %9, %10, %11, %12, %13, %14, %15}, {%16,%17,%18,%19}, db, p, 1, 1, 0;\n}\n"
    : "+f"(d[32]), "+f"(d[33]), "+f"(d[34]), "+f"(d[35]), "+f"(d[36]), "+f"(d[37]), "+f"(d[38]), "+f"(d[39]), "+f"(d[40]), "+f"(d[41]), "+f"(d[42]), "+f"(d[43]), "+f"(d[44]), "+f"(d[45]), "+f"(d[46]), "+f"(d[47]) : "r"(a[0]), "r"(a[1]), "r"(a[2]), "r"(a[3]), "r"(blo));
}
template<> __device__ __forceinline__ void wg_rs32<48,0>(float (&d)[64], const uint32_t* a, uint32_t blo) {
  asm volatile("{\n.reg .pred p;\n.reg .b64 db;\nmov.b64 db, {%20, 8};\nsetp.ne.b32 p, 0, 0;\n"
    "wgmma.mma_async.sync.aligned.m64n32k16.f32.bf16.bf16 {%0, %1, %2, %3, %4, %5, %6, %7, %8, %9, %10, %11, %12, %13, %14, %15}, {%16,%17,%18,%19}, db, p, 1, 1, 0;\n}\n"
    : "+f"(d[48]), "+f"(d[49]), "+f"(d[50]), "+f"(d[51]), "+f"(d[52]), "+f"(d[53]), "+f"(d[54]), "+f"(d[55]), "+f"(d[56]), "+f"(d[57]), "+f"(d[58]), "+f"(d[59]), "+f"(d[60]), "+f"(d[61]), "+f"(d[62]), "+f"(d[63]) : "r"(a[0]), "r"(a[1]), "r"(a[2]), "r"(a[3]), "r"(blo));
}
template<> __device__ __forceinline__ void wg_rs32<48,1>(float (&d)[64], const uint32_t* a, uint32_t blo) {
  asm volatile("{\n.reg .pred p;\n.reg .b64 db;\nmov.b64 db, {%20, 8};\nsetp.ne.b32 p, 1, 0;\n"
    "wgmma.mma_async.sync.aligned.m64n32k16.f32.bf16.bf16 {%0, %1, %2, %3, %4, %5, %6, %7, %8, %9, %10, %11, %12, %13, %14, %15}, {%16,%17,%18,%19}, db, p, 1, 1, 0;\n}\n"
    : "+f"(d[48]), "+f"(d[49]), "+f"(d[50]), "+f"(d[51]), "+f"(d[52]), "+f"(d[53]), "+f"(d[54]), "+f"(d[55]), "+f"(d[56]), "+f"(d[57]), "+f"(d[58]), "+f"(d[59]), "+f"(d[60]), "+f"(d[61]), "+f"(d[62]), "+f"(d[63]) : "r"(a[0]), "r"(a[1]), "r"(a[2]), "r"(a[3]), "r"(blo));
}
template<int OFF, int SC> __device__ __forceinline__ void wg_rs32f(float (&d)[128], const uint32_t* a, uint32_t blo);
template<> __device__ __forceinline__ void wg_rs32f<0,0>(float (&d)[128], const uint32_t* a, uint32_t blo) {
  asm volatile("{\n.reg .pred p;\n.reg .b64 db;\nmov.b64 db, {%20, 8};\nsetp.ne.b32 p, 0, 0;\n"
    "wgmma.mma_async.sync.aligned.m64n32k16.f32.bf16.bf16 {%0, %1, %2, %3, %4, %5, %6, %7, %8, %9, %10, %11, %12, %13, %14, %15}, {%16,%17,%18,%19}, db, p, 1, 1, 0;\n}\n"
    : "+f"(d[0]), "+f"(d[1]), "+f"(d[2]), "+f"(d[3]), "+f"(d[4]), "+f"(d[5]), "+f"(d[6]), "+f"(d[7]), "+f"(d[8]), "+f"(d[9]), "+f"(d[10]), "+f"(d[11]), "+f"(d[12]), "+f"(d[13]), "+f"(d[14]), "+f"(d[15]) : "r"(a[0]), "r"(a[1]), "r"(a[2]), "r"(a[3]), "r"(blo));
}
template<> __device__ __forceinline__ void wg_rs32f<0,1>(float (&d)[128], const uint32_t* a, uint32_t blo) {
  asm volatile("{\n.reg .pred p;\n.reg .b64 db;\nmov.b64 db, {%20, 8};\nsetp.ne.b32 p, 1, 0;\n"
    "wgmma.mma_async.sync.aligned.m64n32k16.f32.bf16.bf16 {%0, %1, %2, %3, %4, %5, %6, %7, %8, %9, %10, %11, %12, %13, %14, %15}, {%16,%17,%18,%19}, db, p, 1, 1, 0;\n}\n"
    : "+f"(d[0]), "+f"(d[1]), "+f"(d[2]), "+f"(d[3]), "+f"(d[4]), "+f"(d[5]), "+f"(d[6]), "+f"(d[7]), "+f"(d[8]), "+f"(d[9]), "+f"(d[10]), "+f"(d[11]), "+f"(d[12]), "+f"(d[13]), "+f"(d[14]), "+f"(d[15]) : "r"(a[0]), "r"(a[1]), "r"(a[2]), "r"(a[3]), "r"(blo));
}
template<> __device__ __forceinline__ void wg_rs32f<16,0>(float (&d)[128], const uint32_t* a, uint32_t blo) {
  asm volatile("{\n.reg .pred p;\n.reg .b64 db;\nmov.b64 db, {%20, 8};\nsetp.ne.b32 p, 0, 0;\n"
    "wgmma.mma_async.sync.aligned.m64n32k16.f32.bf16.bf16 {%0, %1, %2, %3, %4, %5, %6, %7, %8, %9, %10, %11, %12, %13, %14, %15}, {%16,%17,%18,%19}, db, p, 1, 1, 0;\n}\n"
    : "+f"(d[16]), "+f"(d[17]), "+f"(d[18]), "+f"(d[19]), "+f"(d[20]), "+f"(d[21]), "+f"(d[22]), "+f"(d[23]), "+f"(d[24]), "+f"(d[25]), "+f"(d[26]), "+f"(d[27]), "+f"(d[28]), "+f"(d[29]), "+f"(d[30]), "+f"(d[31]) : "r"(a[0]), "r"(a[1]), "r"(a[2]), "r"(a[3]), "r"(blo));
}
template<> __device__ __forceinline__ void wg_rs32f<16,1>(float (&d)[128], const uint32_t* a, uint32_t blo) {
  asm volatile("{\n.reg .pred p;\n.reg .b64 db;\nmov.b64 db, {%20, 8};\nsetp.ne.b32 p, 1, 0;\n"
    "wgmma.mma_async.sync.aligned.m64n32k16.f32.bf16.bf16 {%0, %1, %2, %3, %4, %5, %6, %7, %8, %9, %10, %11, %12, %13, %14, %15}, {%16,%17,%18,%19}, db, p, 1, 1, 0;\n}\n"
    : "+f"(d[16]), "+f"(d[17]), "+f"(d[18]), "+f"(d[19]), "+f"(d[20]), "+f"(d[21]), "+f"(d[22]), "+f"(d[23]), "+f"(d[24]), "+f"(d[25]), "+f"(d[26]), "+f"(d[27]), "+f"(d[28]), "+f"(d[29]), "+f"(d[30]), "+f"(d[31]) : "r"(a[0]), "r"(a[1]), "r"(a[2]), "r"(a[3]), "r"(blo));
}
template<> __device__ __forceinline__ void wg_rs32f<32,0>(float (&d)[128], const uint32_t* a, uint32_t blo) {
  asm volatile("{\n.reg .pred p;\n.reg .b64 db;\nmov.b64 db, {%20, 8};\nsetp.ne.b32 p, 0, 0;\n"
    "wgmma.mma_async.sync.aligned.m64n32k16.f32.bf16.bf16 {%0, %1, %2, %3, %4, %5, %6, %7, %8, %9, %10, %11, %12, %13, %14, %15}, {%16,%17,%18,%19}, db, p, 1, 1, 0;\n}\n"
    : "+f"(d[32]), "+f"(d[33]), "+f"(d[34]), "+f"(d[35]), "+f"(d[36]), "+f"(d[37]), "+f"(d[38]), "+f"(d[39]), "+f"(d[40]), "+f"(d[41]), "+f"(d[42]), "+f"(d[43]), "+f"(d[44]), "+f"(d[45]), "+f"(d[46]), "+f"(d[47]) : "r"(a[0]), "r"(a[1]), "r"(a[2]), "r"(a[3]), "r"(blo));
}
template<> __device__ __forceinline__ void wg_rs32f<32,1>(float (&d)[128], const uint32_t* a, uint32_t blo) {
  asm volatile("{\n.reg .pred p;\n.reg .b64 db;\nmov.b64 db, {%20, 8};\nsetp.ne.b32 p, 1, 0;\n"
    "wgmma.mma_async.sync.aligned.m64n32k16.f32.bf16.bf16 {%0, %1, %2, %3, %4, %5, %6, %7, %8, %9, %10, %11, %12, %13, %14, %15}, {%16,%17,%18,%19}, db, p, 1, 1, 0;\n}\n"
    : "+f"(d[32]), "+f"(d[33]), "+f"(d[34]), "+f"(d[35]), "+f"(d[36]), "+f"(d[37]), "+f"(d[38]), "+f"(d[39]), "+f"(d[40]), "+f"(d[41]), "+f"(d[42]), "+f"(d[43]), "+f"(d[44]), "+f"(d[45]), "+f"(d[46]), "+f"(d[47]) : "r"(a[0]), "r"(a[1]), "r"(a[2]), "r"(a[3]), "r"(blo));
}
template<> __device__ __forceinline__ void wg_rs32f<48,0>(float (&d)[128], const uint32_t* a, uint32_t blo) {
  asm volatile("{\n.reg .pred p;\n.reg .b64 db;\nmov.b64 db, {%20, 8};\nsetp.ne.b32 p, 0, 0;\n"
    "wgmma.mma_async.sync.aligned.m64n32k16.f32.bf16.bf16 {%0, %1, %2, %3, %4, %5, %6, %7, %8, %9, %10, %11, %12, %13, %14, %15}, {%16,%17,%18,%19}, db, p, 1, 1, 0;\n}\n"
    : "+f"(d[48]), "+f"(d[49]), "+f"(d[50]), "+f"(d[51]), "+f"(d[52]), "+f"(d[53]), "+f"(d[54]), "+f"(d[55]), "+f"(d[56]), "+f"(d[57]), "+f"(d[58]), "+f"(d[59]), "+f"(d[60]), "+f"(d[61]), "+f"(d[62]), "+f"(d[63]) : "r"(a[0]), "r"(a[1]), "r"(a[2]), "r"(a[3]), "r"(blo));
}
template<> __device__ __forceinline__ void wg_rs32f<48,1>(float (&d)[128], const uint32_t* a, uint32_t blo) {
  asm volatile("{\n.reg .pred p;\n.reg .b64 db;\nmov.b64 db, {%20, 8};\nsetp.ne.b32 p, 1, 0;\n"
    "wgmma.mma_async.sync.aligned.m64n32k16.f32.bf16.bf16 {%0, %1, %2, %3, %4, %5, %6, %7, %8, %9, %10, %11, %12, %13, %14, %15}, {%16,%17,%18,%19}, db, p, 1, 1, 0;\n}\n"
    : "+f"(d[48]), "+f"(d[49]), "+f"(d[50]), "+f"(d[51]), "+f"(d[52]), "+f"(d[53]), "+f"(d[54]), "+f"(d[55]), "+f"(d[56]), "+f"(d[57]), "+f"(d[58]), "+f"(d[59]), "+f"(d[60]), "+f"(d[61]), "+f"(d[62]), "+f"(d[63]) : "r"(a[0]), "r"(a[1]), "r"(a[2]), "r"(a[3]), "r"(blo));
}
template<> __device__ __forceinline__ void wg_rs32f<64,0>(float (&d)[128], const uint32_t* a, uint32_t blo) {
  asm volatile("{\n.reg .pred p;\n.reg .b64 db;\nmov.b64 db, {%20, 8};\nsetp.ne.b32 p, 0, 0;\n"
    "wgmma.mma_async.sync.aligned.m64n32k16.f32.bf16.bf16 {%0, %1, %2, %3, %4, %5, %6, %7, %8, %9, %10, %11, %12, %13, %14, %15}, {%16,%17,%18,%19}, db, p, 1, 1, 0;\n}\n"
    : "+f"(d[64]), "+f"(d[65]), "+f"(d[66]), "+f"(d[67]), "+f"(d[68]), "+f"(d[69]), "+f"(d[70]), "+f"(d[71]), "+f"(d[72]), "+f"(d[73]), "+f"(d[74]), "+f"(d[75]), "+f"(d[76]), "+f"(d[77]), "+f"(d[78]), "+f"(d[79]) : "r"(a[0]), "r"(a[1]), "r"(a[2]), "r"(a[3]), "r"(blo));
}
template<> __device__ __forceinline__ void wg_rs32f<64,1>(float (&d)[128], const uint32_t* a, uint32_t blo) {
  asm volatile("{\n.reg .pred p;\n.reg .b64 db;\nmov.b64 db, {%20, 8};\nsetp.ne.b32 p, 1, 0;\n"
    "wgmma.mma_async.sync.aligned.m64n32k16.f32.bf16.bf16 {%0, %1, %2, %3, %4, %5, %6, %7, %8, %9, %10, %11, %12, %13, %14, %15}, {%16,%17,%18,%19}, db, p, 1, 1, 0;\n}\n"
    : "+f"(d[64]), "+f"(d[65]), "+f"(d[66]), "+f"(d[67]), "+f"(d[68]), "+f"(d[69]), "+f"(d[70]), "+f"(d[71]), "+f"(d[72]), "+f"(d[73]), "+f"(d[74]), "+f"(d[75]), "+f"(d[76]), "+f"(d[77]), "+f"(d[78]), "+f"(d[79]) : "r"(a[0]), "r"(a[1]), "r"(a[2]), "r"(a[3]), "r"(blo));
}
template<> __device__ __forceinline__ void wg_rs32f<80,0>(float (&d)[128], const uint32_t* a, uint32_t blo) {
  asm volatile("{\n.reg .pred p;\n.reg .b64 db;\nmov.b64 db, {%20, 8};\nsetp.ne.b32 p, 0, 0;\n"
    "wgmma.mma_async.sync.aligned.m64n32k16.f32.bf16.bf16 {%0, %1, %2, %3, %4, %5, %6, %7, %8, %9, %10, %11, %12, %13, %14, %15}, {%16,%17,%18,%19}, db, p, 1, 1, 0;\n}\n"
    : "+f"(d[80]), "+f"(d[81]), "+f"(d[82]), "+f"(d[83]), "+f"(d[84]), "+f"(d[85]), "+f"(d[86]), "+f"(d[87]), "+f"(d[88]), "+f"(d[89]), "+f"(d[90]), "+f"(d[91]), "+f"(d[92]), "+f"(d[93]), "+f"(d[94]), "+f"(d[95]) : "r"(a[0]), "r"(a[1]), "r"(a[2]), "r"(a[3]), "r"(blo));
}
template<> __device__ __forceinline__ void wg_rs32f<80,1>(float (&d)[128], const uint32_t* a, uint32_t blo) {
  asm volatile("{\n.reg .pred p;\n.reg .b64 db;\nmov.b64 db, {%20, 8};\nsetp.ne.b32 p, 1, 0;\n"
    "wgmma.mma_async.sync.aligned.m64n32k16.f32.bf16.bf16 {%0, %1, %2, %3, %4, %5, %6, %7, %8, %9, %10, %11, %12, %13, %14, %15}, {%16,%17,%18,%19}, db, p, 1, 1, 0;\n}\n"
    : "+f"(d[80]), "+f"(d[81]), "+f"(d[82]), "+f"(d[83]), "+f"(d[84]), "+f"(d[85]), "+f"(d[86]), "+f"(d[87]), "+f"(d[88]), "+f"(d[89]), "+f"(d[90]), "+f"(d[91]), "+f"(d[92]), "+f"(d[93]), "+f"(d[94]), "+f"(d[95]) : "r"(a[0]), "r"(a[1]), "r"(a[2]), "r"(a[3]), "r"(blo));
}
template<> __device__ __forceinline__ void wg_rs32f<96,0>(float (&d)[128], const uint32_t* a, uint32_t blo) {
  asm volatile("{\n.reg .pred p;\n.reg .b64 db;\nmov.b64 db, {%20, 8};\nsetp.ne.b32 p, 0, 0;\n"
    "wgmma.mma_async.sync.aligned.m64n32k16.f32.bf16.bf16 {%0, %1, %2, %3, %4, %5, %6, %7, %8, %9, %10, %11, %12, %13, %14, %15}, {%16,%17,%18,%19}, db, p, 1, 1, 0;\n}\n"
    : "+f"(d[96]), "+f"(d[97]), "+f"(d[98]), "+f"(d[99]), "+f"(d[100]), "+f"(d[101]), "+f"(d[102]), "+f"(d[103]), "+f"(d[104]), "+f"(d[105]), "+f"(d[106]), "+f"(d[107]), "+f"(d[108]), "+f"(d[109]), "+f"(d[110]), "+f"(d[111]) : "r"(a[0]), "r"(a[1]), "r"(a[2]), "r"(a[3]), "r"(blo));
}
template<> __device__ __forceinline__ void wg_rs32f<96,1>(float (&d)[128], const uint32_t* a, uint32_t blo) {
  asm volatile("{\n.reg .pred p;\n.reg .b64 db;\nmov.b64 db, {%20, 8};\nsetp.ne.b32 p, 1, 0;\n"
    "wgmma.mma_async.sync.aligned.m64n32k16.f32.bf16.bf16 {%0, %1, %2, %3, %4, %5, %6, %7, %8, %9, %10, %11, %12, %13, %14, %15}, {%16,%17,%18,%19}, db, p, 1, 1, 0;\n}\n"
    : "+f"(d[96]), "+f"(d[97]), "+f"(d[98]), "+f"(d[99]), "+f"(d[100]), "+f"(d[101]), "+f"(d[102]), "+f"(d[103]), "+f"(d[104]), "+f"(d[105]), "+f"(d[106]), "+f"(d[107]), "+f"(d[108]), "+f"(d[109]), "+f"(d[110]), "+f"(d[111]) : "r"(a[0]), "r"(a[1]), "r"(a[2]), "r"(a[3]), "r"(blo));
}
template<> __device__ __forceinline__ void wg_rs32f<112,0>(float (&d)[128], const uint32_t* a, uint32_t blo) {
  asm volatile("{\n.reg .pred p;\n.reg .b64 db;\nmov.b64 db, {%20, 8};\nsetp.ne.b32 p, 0, 0;\n"
    "wgmma.mma_async.sync.aligned.m64n32k16.f32.bf16.bf16 {%0, %1, %2, %3, %4, %5, %6, %7, %8, %9, %10, %11, %12, %13, %14, %15}, {%16,%17,%18,%19}, db, p, 1, 1, 0;\n}\n"
    : "+f"(d[112]), "+f"(d[113]), "+f"(d[114]), "+f"(d[115]), "+f"(d[116]), "+f"(d[117]), "+f"(d[118]), "+f"(d[119]), "+f"(d[120]), "+f"(d[121]), "+f"(d[122]), "+f"(d[123]), "+f"(d[124]), "+f"(d[125]), "+f"(d[126]), "+f"(d[127]) : "r"(a[0]), "r"(a[1]), "r"(a[2]), "r"(a[3]), "r"(blo));
}
template<> __device__ __forceinline__ void wg_rs32f<112,1>(float (&d)[128], const uint32_t* a, uint32_t blo) {
  asm volatile("{\n.reg .pred p;\n.reg .b64 db;\nmov.b64 db, {%20, 8};\nsetp.ne.b32 p, 1, 0;\n"
    "wgmma.mma_async.sync.aligned.m64n32k16.f32.bf16.bf16 {%0, %1, %2, %3, %4, %5, %6, %7, %8, %9, %10, %11, %12, %13, %14, %15}, {%16,%17,%18,%19}, db, p, 1, 1, 0;\n}\n"
    : "+f"(d[112]), "+f"(d[113]), "+f"(d[114]), "+f"(d[115]), "+f"(d[116]), "+f"(d[117]), "+f"(d[118]), "+f"(d[119]), "+f"(d[120]), "+f"(d[121]), "+f"(d[122]), "+f"(d[123]), "+f"(d[124]), "+f"(d[125]), "+f"(d[126]), "+f"(d[127]) : "r"(a[0]), "r"(a[1]), "r"(a[2]), "r"(a[3]), "r"(blo));
}
template<int OFF, int SC> __device__ __forceinline__ void wg_rs64(float (&d)[64], const uint32_t* a, uint32_t blo);
template<> __device__ __forceinline__ void wg_rs64<0,0>(float (&d)[64], const uint32_t* a, uint32_t blo) {
  asm volatile("{\n.reg .pred p;\n.reg .b64 db;\nmov.b64 db, {%36, 8};\nsetp.ne.b32 p, 0, 0;\n"
    "wgmma.mma_async.sync.aligned.m64n64k16.f32.bf16.bf16 {%0, %1, %2, %3, %4, %5, %6, %7, %8, %9, %10, %11, %12, %13, %14, %15, %16, %17, %18, %19, %20, %21, %22, %23, %24, %25, %26, %27, %28, %29, %30, %31}, {%32,%33,%34,%35}, db, p, 1, 1, 0;\n}\n"
    : "+f"(d[0]), "+f"(d[1]), "+f"(d[2]), "+f"(d[3]), "+f"(d[4]), "+f"(d[5]), "+f"(d[6]), "+f"(d[7]), "+f"(d[8]), "+f"(d[9]), "+f"(d[10]), "+f"(d[11]), "+f"(d[12]), "+f"(d[13]), "+f"(d[14]), "+f"(d[15]), "+f"(d[16]), "+f"(d[17]), "+f"(d[18]), "+f"(d[19]), "+f"(d[20]), "+f"(d[21]), "+f"(d[22]), "+f"(d[23]), "+f"(d[24]), "+f"(d[25]), "+f"(d[26]), "+f"(d[27]), "+f"(d[28]), "+f"(d[29]), "+f"(d[30]), "+f"(d[31]) : "r"(a[0]), "r"(a[1]), "r"(a[2]), "r"(a[3]), "r"(blo));
}
template<> __device__ __forceinline__ void wg_rs64<0,1>(float (&d)[64], const uint32_t* a, uint32_t blo) {
  asm volatile("{\n.reg .pred p;\n.reg .b64 db;\nmov.b64 db, {%36, 8};\nsetp.ne.b32 p, 1, 0;\n"
    "wgmma.mma_async.sync.aligned.m64n64k16.f32.bf16.bf16 {%0, %1, %2, %3, %4, %5, %6, %7, %8, %9, %10, %11, %12, %13, %14, %15, %16, %17, %18, %19, %20, %21, %22, %23, %24, %25, %26, %27, %28, %29, %30, %31}, {%32,%33,%34,%35}, db, p, 1, 1, 0;\n}\n"
    : "+f"(d[0]), "+f"(d[1]), "+f"(d[2]), "+f"(d[3]), "+f"(d[4]), "+f"(d[5]), "+f"(d[6]), "+f"(d[7]), "+f"(d[8]), "+f"(d[9]), "+f"(d[10]), "+f"(d[11]), "+f"(d[12]), "+f"(d[13]), "+f"(d[14]), "+f"(d[15]), "+f"(d[16]), "+f"(d[17]), "+f"(d[18]), "+f"(d[19]), "+f"(d[20]), "+f"(d[21]), "+f"(d[22]), "+f"(d[23]), "+f"(d[24]), "+f"(d[25]), "+f"(d[26]), "+f"(d[27]), "+f"(d[28]), "+f"(d[29]), "+f"(d[30]), "+f"(d[31]) : "r"(a[0]), "r"(a[1]), "r"(a[2]), "r"(a[3]), "r"(blo));
}
template<> __device__ __forceinline__ void wg_rs64<32,0>(float (&d)[64], const uint32_t* a, uint32_t blo) {
  asm volatile("{\n.reg .pred p;\n.reg .b64 db;\nmov.b64 db, {%36, 8};\nsetp.ne.b32 p, 0, 0;\n"
    "wgmma.mma_async.sync.aligned.m64n64k16.f32.bf16.bf16 {%0, %1, %2, %3, %4, %5, %6, %7, %8, %9, %10, %11, %12, %13, %14, %15, %16, %17, %18, %19, %20, %21, %22, %23, %24, %25, %26, %27, %28, %29, %30, %31}, {%32,%33,%34,%35}, db, p, 1, 1, 0;\n}\n"
    : "+f"(d[32]), "+f"(d[33]), "+f"(d[34]), "+f"(d[35]), "+f"(d[36]), "+f"(d[37]), "+f"(d[38]), "+f"(d[39]), "+f"(d[40]), "+f"(d[41]), "+f"(d[42]), "+f"(d[43]), "+f"(d[44]), "+f"(d[45]), "+f"(d[46]), "+f"(d[47]), "+f"(d[48]), "+f"(d[49]), "+f"(d[50]), "+f"(d[51]), "+f"(d[52]), "+f"(d[53]), "+f"(d[54]), "+f"(d[55]), "+f"(d[56]), "+f"(d[57]), "+f"(d[58]), "+f"(d[59]), "+f"(d[60]), "+f"(d[61]), "+f"(d[62]), "+f"(d[63]) : "r"(a[0]), "r"(a[1]), "r"(a[2]), "r"(a[3]), "r"(blo));
}
template<> __device__ __forceinline__ void wg_rs64<32,1>(float (&d)[64], const uint32_t* a, uint32_t blo) {
  asm volatile("{\n.reg .pred p;\n.reg .b64 db;\nmov.b64 db, {%36, 8};\nsetp.ne.b32 p, 1, 0;\n"
    "wgmma.mma_async.sync.aligned.m64n64k16.f32.bf16.bf16 {%0, %1, %2, %3, %4, %5, %6, %7, %8, %9, %10, %11, %12, %13, %14, %15, %16, %17, %18, %19, %20, %21, %22, %23, %24, %25, %26, %27, %28, %29, %30, %31}, {%32,%33,%34,%35}, db, p, 1, 1, 0;\n}\n"
    : "+f"(d[32]), "+f"(d[33]), "+f"(d[34]), "+f"(d[35]), "+f"(d[36]), "+f"(d[37]), "+f"(d[38]), "+f"(d[39]), "+f"(d[40]), "+f"(d[41]), "+f"(d[42]), "+f"(d[43]), "+f"(d[44]), "+f"(d[45]), "+f"(d[46]), "+f"(d[47]), "+f"(d[48]), "+f"(d[49]), "+f"(d[50]), "+f"(d[51]), "+f"(d[52]), "+f"(d[53]), "+f"(d[54]), "+f"(d[55]), "+f"(d[56]), "+f"(d[57]), "+f"(d[58]), "+f"(d[59]), "+f"(d[60]), "+f"(d[61]), "+f"(d[62]), "+f"(d[63]) : "r"(a[0]), "r"(a[1]), "r"(a[2]), "r"(a[3]), "r"(blo));
}

struct Params {
  const __nv_bfloat16 *k, *v, *h;
  Scratch* s;
  const __nv_bfloat16 *shift, *dv, *x, *w1, *b1, *b2;
  __nv_bfloat16* out;
};

__device__ __forceinline__ void mma16816(float (&c)[4], uint32_t a0, uint32_t a1, uint32_t a2, uint32_t a3, uint32_t b0, uint32_t b1) {
  asm("mma.sync.aligned.m16n8k16.row.col.f32.bf16.bf16.f32 {%0,%1,%2,%3}, {%4,%5,%6,%7}, {%8,%9}, {%0,%1,%2,%3};"
               : "+f"(c[0]), "+f"(c[1]), "+f"(c[2]), "+f"(c[3]) : "r"(a0), "r"(a1), "r"(a2), "r"(a3), "r"(b0), "r"(b1));
}
__device__ __forceinline__ void ln_rows(uint32_t src, float4* stat, int nrows, unsigned ep, int lane) {
  const int g = lane >> 2, t4 = lane & 3;
  uint32_t a = src + g * 1280 + t4 * 16 + (g & 1) * 64, b = a ^ 64;
  asm volatile("" : "+r"(a), "+r"(b) :: "memory");
  const uint32_t one = 0x3F803F80u;
  float s0[4] = {0.f, 0.f, 0.f, 0.f}, s1[4] = {0.f, 0.f, 0.f, 0.f};
#pragma unroll
  for (int j = 0; j < 20; j++) {
    const uint4 u = lds128_ro(((j & 1) ? b : a) + (j >> 1) * 128), v = lds128_ro(((j & 1) ? b : a) + 8 * 1280 + (j >> 1) * 128);
    mma16816(s0, u.x, v.x, u.y, v.y, one, one);
    mma16816(s1, u.z, v.z, u.w, v.w, one, one);
  }
  const float m0 = (s0[0] + s1[0]) * (1.f / D_), m1 = (s0[2] + s1[2]) * (1.f / D_);
  const uint32_t p0 = pack2(m0, m0), p1 = pack2(m1, m1);
  float q0[4] = {0.f, 0.f, 0.f, 0.f}, q1[4] = {0.f, 0.f, 0.f, 0.f}, q2[4] = {0.f, 0.f, 0.f, 0.f}, q3[4] = {0.f, 0.f, 0.f, 0.f};
  s0[0] = s0[1] = s0[2] = s0[3] = s1[0] = s1[1] = s1[2] = s1[3] = 0.f;
  asm volatile("" : "+r"(a), "+r"(b) :: "memory");
#pragma unroll 4
  for (int j = 0; j < 20; j++) {
    uint4 u = lds128_ro(((j & 1) ? b : a) + (j >> 1) * 128), v = lds128_ro(((j & 1) ? b : a) + 8 * 1280 + (j >> 1) * 128);
    u.x = hsub2(u.x, p0); u.y = hsub2(u.y, p0); u.z = hsub2(u.z, p0); u.w = hsub2(u.w, p0);
    v.x = hsub2(v.x, p1); v.y = hsub2(v.y, p1); v.z = hsub2(v.z, p1); v.w = hsub2(v.w, p1);
    mma16816(q0, u.x, v.x, u.y, v.y, u.x, u.y);
    mma16816(q1, u.x, v.x, u.y, v.y, v.x, v.y);
    mma16816(q2, u.z, v.z, u.w, v.w, u.z, u.w);
    mma16816(q3, u.z, v.z, u.w, v.w, v.z, v.w);
    mma16816(s0, u.x, v.x, u.y, v.y, one, one);
    mma16816(s1, u.z, v.z, u.w, v.w, one, one);
  }
  if (t4 == (g >> 1)) {
    const float r0 = (s0[0] + s1[0]) * (1.f / D_), r1 = (s0[2] + s1[2]) * (1.f / D_);
    const float v0 = ((g & 1) ? q0[1] + q2[1] : q0[0] + q2[0]) * (1.f / D_) - r0 * r0;
    const float v1 = ((g & 1) ? q1[3] + q3[3] : q1[2] + q3[2]) * (1.f / D_) - r1 * r1;
    if (g < nrows) stg128(stat + g, __float_as_uint(m0), __float_as_uint(rsqrt_fast(fmaxf(v0, 0.f) + 1e-5f)), ep, 0u);
    if (g + 8 < nrows) stg128(stat + g + 8, __float_as_uint(m1), __float_as_uint(rsqrt_fast(fmaxf(v1, 0.f) + 1e-5f)), ep, 0u);
  }
}

struct KvJob { uint2 kk[11], vv[8]; uint4 s0, s1; };
__device__ __forceinline__ void kv_load(const Params& P, int unit, int lane, KvJob& J) {
  const int t0 = (unit & 127) * 16 + (lane >> 4) * 8, c = (unit >> 7) * 64 + (lane & 15) * 4;
  const __nv_bfloat16* kp = P.k + (size_t)t0 * D_ + c;
  const __nv_bfloat16* vp = P.v + (size_t)t0 * D_ + c;
#pragma unroll
  for (int j = 0; j < 11; j++) { J.kk[j] = make_uint2(0u, 0u); if (j >= 3 || t0 > 0) J.kk[j] = ldg64(kp + (j - 3) * D_); }
#pragma unroll
  for (int j = 0; j < 8; j++) J.vv[j] = ldg64(vp + j * D_);
  J.s0 = __ldg((const uint4*)(P.shift + c * 4)); J.s1 = __ldg((const uint4*)(P.shift + c * 4 + 8));
}
__device__ __forceinline__ void kv_finish(const KvJob& J, uint32_t a, int d1, int d2, int d3) {
  const uint32_t wa[4] = {__byte_perm(J.s0.x, J.s0.z, 0x5410), __byte_perm(J.s0.x, J.s0.z, 0x7632), __byte_perm(J.s0.y, J.s0.w, 0x5410), __byte_perm(J.s0.y, J.s0.w, 0x7632)};
  const uint32_t wb[4] = {__byte_perm(J.s1.x, J.s1.z, 0x5410), __byte_perm(J.s1.x, J.s1.z, 0x7632), __byte_perm(J.s1.y, J.s1.w, 0x5410), __byte_perm(J.s1.y, J.s1.w, 0x7632)};
  uint32_t ra[8], rb[8];
#pragma unroll
  for (int j = 0; j < 8; j++) {
    ra[j] = hmul2(hfma2(J.kk[j + 3].x, wa[0], hfma2(J.kk[j + 2].x, wa[1], hfma2(J.kk[j + 1].x, wa[2], hmul2(J.kk[j].x, wa[3])))), J.vv[j].x);
    rb[j] = hmul2(hfma2(J.kk[j + 3].y, wb[0], hfma2(J.kk[j + 2].y, wb[1], hfma2(J.kk[j + 1].y, wb[2], hmul2(J.kk[j].y, wb[3])))), J.vv[j].y);
  }
  const uint32_t* src[4] = {ra, ra, rb, rb};
  const int off[4] = {0, d1, d2, d3};
#pragma unroll
  for (int c = 0; c < 4; c++) {
    const uint32_t sel = (c & 1) ? 0x7632 : 0x5410, *r = src[c];
    const uint32_t w0 = __byte_perm(r[7], r[6], sel), w1 = __byte_perm(r[5], r[4], sel), w2 = __byte_perm(r[3], r[2], sel), w3 = __byte_perm(r[1], r[0], sel);
    sts128(a + off[c], w0, w1, w2, w3);
  }
}

template <int J> __device__ __forceinline__ void ldp(uint32_t* p, uint32_t pa) {
  p[0] = lds32(pa + 256 * J); p[1] = lds32(pa + 256 * J + 128); p[2] = lds32(pa + 256 * J + 16); p[3] = lds32(pa + 256 * J + 144);
}
template <int J, int BASE> __device__ __forceinline__ void cstep(float (&d)[64], const uint32_t* a, uint32_t db) {
  if (BASE + 96 < 256 - 16 * J) wg_rs32<48, (J != 0)>(d, a, db + (J * 16 + BASE + 96));
  if (BASE + 64 < 256 - 16 * J) wg_rs32<32, (J != 0)>(d, a, db + (J * 16 + BASE + 64));
  if (BASE + 32 < 256 - 16 * J) wg_rs32<16, (J != 0)>(d, a, db + (J * 16 + BASE + 32));
  if (BASE < 256 - 16 * J) wg_rs32<0, (J != 0)>(d, a, db + (J * 16 + BASE));
}
template <int JN> __device__ __forceinline__ void csend(float (&d)[64], uint32_t sa, uint32_t carry, bool sh) {
  constexpr int JL = JN & 15;
  float v0 = d[4 * JL], v1 = d[4 * JL + 1];
  if (JL < 15) { v0 += d[4 * JL + 6]; v1 += d[4 * JL + 7]; }
  uint32_t v = pack2(v0, v1);
  if (JN == 15) v = hadd2(v, carry);
  if (JN == 0) sts32p(sa, v, !sh); else sts32(sa + JN * 128, v);
}
#define CSEND8(B, CARRY) csend<B + 7>(d, sa, CARRY, sh); csend<B + 6>(d, sa, 0, sh); csend<B + 5>(d, sa, 0, sh); csend<B + 4>(d, sa, 0, sh); \
                         csend<B + 3>(d, sa, 0, sh); csend<B + 2>(d, sa, 0, sh); csend<B + 1>(d, sa, 0, sh); csend<B>(d, sa, 0, sh)

__device__ __forceinline__ void conv_issue_u(const Params& P, int ch, uint32_t dst, uint32_t bar, unsigned ep, unsigned seen = 0) {
  if ((int)(seen - ep * 128) < 0) flag_wait(P.s->cnt, C_KV + (ch >> 6), ep * 128);
  fence_async();
  mbar_expect(bar, 4096);
  bulk_g2s(dst, P.s->ur + (size_t)ch * S_, 4096, bar);
}

struct HJob { uint4 v0, v1; uint32_t n0, n1, dv; };
__device__ __forceinline__ void h_load(const Params& P, int ch, int c0, HJob& H) {
  const __nv_bfloat16* hp = P.h + (size_t)ch * S_ + c0 * 8;
  H.v0 = ldg128(hp); H.v1 = ldg128(hp + 256);
  H.n0 = ldg32(hp + 8); H.n1 = 0;
  if (c0 + 33 < 256) H.n1 = ldg32(hp + 264);
  H.dv = 0;
  if (c0 == 0) asm volatile("ld.global.nc.u16 %0, [%1];" : "=r"(H.dv) : "l"(P.dv + ch));
}
__device__ __forceinline__ void h_store(uint32_t st, int c0, HJob& H) {
  H.v0.x = __byte_perm(pack2(bf_lo(H.v0.x) + bf_lo(H.dv), 0.f), H.v0.x, 0x7610);
  if (c0 == 0) sts128(st + ST_H1, 0, 0, 0, H.v0.x << 16);
  sts128(st + ST_H0 + 16 + 16 * c0, H.v0.x, H.v0.y, H.v0.z, H.v0.w);
  sts128(st + ST_H1 + 16 + 16 * c0, __byte_perm(H.v0.x, H.v0.y, 0x5432), __byte_perm(H.v0.y, H.v0.z, 0x5432), __byte_perm(H.v0.z, H.v0.w, 0x5432), __byte_perm(H.v0.w, H.n0, 0x5432));
  sts128(st + ST_H0 + 528 + 16 * c0, H.v1.x, H.v1.y, H.v1.z, H.v1.w);
  sts128(st + ST_H1 + 528 + 16 * c0, __byte_perm(H.v1.x, H.v1.y, 0x5432), __byte_perm(H.v1.y, H.v1.z, 0x5432), __byte_perm(H.v1.z, H.v1.w, 0x5432), __byte_perm(H.v1.w, H.n1, 0x5432));
}
__device__ __forceinline__ void zero_pads(uint32_t st, int nst, int tid) {
  if (tid < 25 * nst) sts128(st + (tid >= 25 ? ST_BYTES - 400 : 0) + 4096 + tid * 16, 0, 0, 0, 0);
}
__device__ __forceinline__ void zero_xch(uint32_t xa, int l) { sts128(xa + (l >> 3) * 4096 + 3968 + (l & 7) * 16, 0, 0, 0, 0); }

__device__ __forceinline__ void conv_run(const Params& P, int ch0, int ch1, int ch2, int ch3, int nloc, uint32_t ux, int n, uint32_t xa, uint32_t yb, uint32_t st0, int nst, uint32_t ubar,
                                         int barid, unsigned ep, int warp, int lane) {
  const int g = lane >> 2, t4 = lane & 3;
  const int y0 = 16 * warp - 7 + g + 2 * t4;
  const uint32_t poff = (g & 1) ? (ST_H0 + 16 + y0 * 2) : (ST_H1 + 16 + (y0 - 1) * 2);
  const bool sh = t4 < warp;
  const uint32_t sa = xa + warp * 4096 + (lane & ~3) * 4 + (((t4 - warp) & 3) << 2) - (sh ? 128 : 0);
  const uint32_t rb = xa + warp * 1024 + lane * 4;
  const uint32_t ya = yb + (255 - (64 * warp + lane)) * 16;
  const int c0 = warp * 64 + lane;
  float d[64];
  int ch = ch0;
#pragma unroll 1
  for (int m = 0; m < n; m++) {
    const int nch = m == 0 ? ch1 : m == 1 ? ch2 : ch3;
    const int s = m & (nst - 1), s1 = (m + 1) & (nst - 1);
    const uint32_t st = st0 + s * ST_BYTES, st1 = st0 + s1 * ST_BYTES;
    HJob H;
    unsigned fl = 0;
    if (m + 1 < n) {
      h_load(P, nch, c0, H);
      asm volatile("ld.relaxed.gpu.global.u32 %0, [%1];" : "=r"(fl) : "l"(P.s->cnt + (C_KV + (nch >> 6)) * 32) : "memory");
    }
    const uint32_t db = (((m == 2 && nloc == 3 ? ux : st + ST_U) & 0x3FFFF) >> 4) | (1u << 16);
    const uint32_t pa = st + poff;
    uint32_t p[32];
    ldp<0>(p, pa); ldp<1>(p + 4, pa); ldp<2>(p + 8, pa); ldp<3>(p + 12, pa);
    if (m < 1 || m >= nloc) mbar_wait(ubar + 8 * s, nst == 2 ? (m == 2) : m & 1);
    wg_fence(); cstep<0, 128>(d, p, db); cstep<1, 128>(d, p + 4, db); cstep<2, 128>(d, p + 8, db); cstep<3, 128>(d, p + 12, db); wg_commit();
    ldp<4>(p + 16, pa); ldp<5>(p + 20, pa); ldp<6>(p + 24, pa); ldp<7>(p + 28, pa);
    wg_fence(); cstep<4, 128>(d, p + 16, db); cstep<5, 128>(d, p + 20, db); cstep<6, 128>(d, p + 24, db); cstep<7, 128>(d, p + 28, db); wg_commit();
    wg_wait<1>();
    CSEND8(24, 0);
    wg_wait<0>();
    CSEND8(16, 0);
    const uint32_t carry = pack2(d[2], d[3]);
    wg_fence(); cstep<0, 0>(d, p, db); cstep<1, 0>(d, p + 4, db); cstep<2, 0>(d, p + 8, db); cstep<3, 0>(d, p + 12, db); wg_commit();
    cstep<4, 0>(d, p + 16, db); cstep<5, 0>(d, p + 20, db); cstep<6, 0>(d, p + 24, db); cstep<7, 0>(d, p + 28, db); wg_commit();
    if (warp == 1 && m == 0 && nloc == 2 && elect()) { bulk_wait<0>(); flag_add_relaxed(P.s->cnt, C_INIT); }
    if (warp == 0 && elect()) {
      bulk_wait_read<0>();
      if (nst == 2 && m + 1 < n && m + 1 >= nloc) conv_issue_u(P, nch, st1 + ST_U, ubar + 8 * s1, ep, fl);
    }
    wg_wait<1>();
    ldp<8>(p, pa); ldp<9>(p + 4, pa); ldp<10>(p + 8, pa); ldp<11>(p + 12, pa);
    wg_fence(); cstep<8, 0>(d, p, db); cstep<9, 0>(d, p + 4, db); cstep<10, 0>(d, p + 8, db); cstep<11, 0>(d, p + 12, db); wg_commit();
    wg_wait<1>();
    ldp<12>(p + 16, pa); ldp<13>(p + 20, pa); ldp<14>(p + 24, pa); ldp<15>(p + 28, pa);
    wg_fence(); cstep<12, 0>(d, p + 16, db); cstep<13, 0>(d, p + 20, db); cstep<14, 0>(d, p + 24, db); cstep<15, 0>(d, p + 28, db); wg_commit();
    wg_wait<1>();
    CSEND8(8, carry);
    wg_wait<0>();
    if (nst == 1 && n == 3 && m == 1) bar_arrive(12, 256);
    CSEND8(0, 0);
    bar_sync(barid, 128);
    if (warp == 0 && nst == 1 && m + 1 < n && elect()) conv_issue_u(P, nch, st + ST_U, ubar, ep, fl);
    uint32_t y[8];
#pragma unroll
    for (int q = 0; q < 8; q++) {
      const uint32_t r0 = lds32(rb + q * 128), r1 = lds32(rb + 4096 + q * 128), r2 = lds32(rb + 8192 + q * 128), r3 = lds32(rb + 12288 + q * 128);
      y[q] = hadd2(hadd2(r0, r1), hadd2(r2, r3));
    }
    stsm4t(ya, y[0], y[1], y[2], y[3]);
    stsm4t(ya - 512, y[4], y[5], y[6], y[7]);
    if (m + 1 < n) h_store(st1, c0, H);
    fence_async_smem();
    bar_sync(barid, 128);
    if (warp == 0 && elect()) { bulk_s2g(P.s->yt + (size_t)ch * S_, yb, 4096); bulk_commit(); }
    ch = nch;
  }
  if (warp == 0) {
    if (elect()) bulk_wait<0>();
    __syncwarp();
    if (lane < n) flag_add_relaxed(P.s->cnt, C_Y + ((lane == 0 ? ch0 : lane == 1 ? ch1 : lane == 2 ? ch2 : ch3) >> 7));
  }
}

__global__ void __cluster_dims__(2, 1, 1) __launch_bounds__(NTHR, 1)
fused_kernel(const Params P, const __grid_constant__ CUtensorMap tm_x, const __grid_constant__ CUtensorMap tm_x64,
             const __grid_constant__ CUtensorMap tm_w1, const __grid_constant__ CUtensorMap tm_w2,
             const __grid_constant__ CUtensorMap tm_out, const __grid_constant__ CUtensorMap tm_yt,
             const __grid_constant__ CUtensorMap tm_k8, const __grid_constant__ CUtensorMap tm_v8,
             const __grid_constant__ CUtensorMap tm_ur) {
  const uint32_t sb = smem_u32(smem_raw);
  const uint32_t bars = sb + OFF_BAR;
  const int wgi = __shfl_sync(~0u, threadIdx.x >> 7, 0), warp = __shfl_sync(~0u, (threadIdx.x >> 5) & 3, 0), lane = threadIdx.x & 31;
  const int cl = blockIdx.x >> 1, rank = blockIdx.x & 1;
  const bool is_conv = cl >= CONV_CL0 && cl < CONV_CL0 + CONV_NCL;
  const int ci = blockIdx.x - 2 * CONV_CL0;
  const int mc = cl < CONV_CL0 ? cl : cl - CONV_NCL;
  const int f = mc >> 3, mt = 2 * (mc & 7) + rank;
  const int mi = 2 * mc + rank;

  if (wgi == 1 && warp == 3) asm volatile("prefetch.global.L2 [%0];" :: "l"(lane < 10 ? P.b2 + lane * 64 : P.b1 + (lane - 10) * 64));
  if (wgi == 0 && warp == 0 && elect()) {
    mbar_init(bars + 8 * B_WF, 1);
    if (!is_conv) {
      mbar_expect(bars + 8 * B_WF, 49152);
      tma_ld(sb + OFF_X, &tm_x, 0, mt * 128, bars + 8 * B_WF);
      tma_ld3(sb + OFF_W, &tm_w1, 0, f * 4, bars + 8 * B_WF);
      tma_ld3(sb + OFF_W + 16384, &tm_w1, 0, f * 4 + 2, bars + 8 * B_WF);
    }
    if (is_conv) {
      mbar_init(bars + 8 * (B_KV + 1), 1); mbar_init(bars + 8 * B_LN, 1);
      const int p0 = ci * 3 < 52 ? 30 * ci : 52 + 27 * ci, p1 = ci * 3 + 3 < 52 ? 30 * ci + 30 : 52 + 27 * ci + 27;
      mbar_expect(bars + 8 * B_LN, (p1 - p0) * 2560);
      bulk_g2s(sb + CV_LN, P.x + (size_t)p0 * 2 * D_, (p1 - p0) * 2560, bars + 8 * B_LN);
      mbar_expect(bars + 8 * B_KV, 32768);
      tma_ld3x(sb, &tm_k8, ci * 8, 0, bars + 8 * B_KV);
      tma_ld3x(sb + 32768, &tm_v8, ci * 8, 0, bars + 8 * B_KV);
      mbar_expect(bars + 8 * (B_KV + 1), 32768);
      tma_ld3x(sb + 16384, &tm_k8, ci * 8, 128, bars + 8 * (B_KV + 1));
      tma_ld3x(sb + 49152, &tm_v8, ci * 8, 128, bars + 8 * (B_KV + 1));
    }
#pragma unroll
    for (int b = 1; b < B_NUM; b++) if (b > B_LN || !is_conv) mbar_init(bars + 8 * b, b >= B_WE && b < B_BEXT ? 4 : b == B_XT ? 2 : 1);
  }
  asm volatile("fence.mbarrier_init.release.cluster;" ::: "memory");
  __syncthreads();
  cluster_arrive();

  if (is_conv || wgi == 2) {
    const int tid = warp * 32 + lane;
    const uint32_t xa = is_conv ? sb + CV_X + wgi * 16384 : sb + OFF_C, yb = is_conv ? sb + CV_Y + wgi * 4096 : xa + 16384;
    const uint32_t st0 = is_conv ? sb + CV_ST + wgi * 2 * ST_BYTES : xa + 20480, ubar = bars + 8 * (B_U + (is_conv ? 2 * wgi : 0));
    const int ch0 = is_conv ? ci * 8 + wgi : 432 + mi;
    const int ch1 = is_conv ? ch0 + 3 : ch0 + 96, ch2 = is_conv ? (wgi < 2 ? ch0 + 6 : 288 + ci) : ch0 + 112, ch3 = 324 + 3 * ci + wgi;
    cluster_wait();
    zero_pads(st0, is_conv ? 2 : 1, tid);
    if (is_conv && wgi == 2 && tid >= 64 && tid < 112) sts128(sb + CV_UX + (tid >= 88 ? ST_H0 - 384 : 0) + 4096 + (tid - 64) * 16, 0, 0, 0, 0);
    fence_async_smem();
    unsigned ep;
    asm volatile("ld.relaxed.gpu.global.u32 %0, [%1];" : "=r"(ep) : "l"(P.s->cnt + C_EPOCH * 32) : "memory");
    HJob H;
    KvJob K, K1;
    const int unit = 512 + warp * 96 + mi;
    if (is_conv) {
      const int p0 = ci * 3 < 52 ? 30 * ci : 52 + 27 * ci, p1 = ci * 3 + 3 < 52 ? 30 * ci + 30 : 52 + 27 * ci + 27;
      h_load(P, ch0, warp * 64 + lane, H);
      if (wgi < 2) {
        const __nv_bfloat16* tp = P.shift + ci * 32;
        K.s0 = __ldg((const uint4*)tp); K.s1 = __ldg((const uint4*)(tp + 8)); K1.s0 = __ldg((const uint4*)(tp + 16)); K1.s1 = __ldg((const uint4*)(tp + 24));
        h_store(st0, warp * 64 + lane, H);
        ep = __shfl_sync(~0u, ep, 0) + 1;
        mbar_wait(bars + 8 * B_KV, 0);
        if (wgi) mbar_wait(bars + 8 * (B_KV + 1), 0);
        const uint32_t ka = sb + wgi * 16384 + tid * 16, kp = tid ? ka - 16 : sb + 127 * 16;
#pragma unroll
        for (int j = 0; j < 11; j++) {
          uint4 t = lds128(j < 3 ? kp + (5 + j) * 2048 : ka + (j - 3) * 2048);
          if (j < 3 && tid + wgi == 0) t = make_uint4(0u, 0u, 0u, 0u);
          K.kk[j] = make_uint2(t.x, t.y); K1.kk[j] = make_uint2(t.z, t.w);
        }
#pragma unroll
        for (int j = 0; j < 8; j++) { const uint4 t = lds128(ka + 32768 + j * 2048); K.vv[j] = make_uint2(t.x, t.y); K1.vv[j] = make_uint2(t.z, t.w); }
        const uint32_t ua = sb + CV_ST + (255 - wgi * 128 - tid) * 16;
        kv_finish(K, ua, 2 * ST_BYTES, 4 * ST_BYTES, ST_BYTES);
        kv_finish(K1, ua + 3 * ST_BYTES, 2 * ST_BYTES, CV_UX - CV_ST - 3 * ST_BYTES, CV_UX - CV_ST - 3 * ST_BYTES + ST_H0);
        fence_async_smem();
        bar_sync(11, 256);
        if (wgi == 1 && warp < 3) zero_xch(sb + CV_X + warp * 16384, lane);
        bar_sync(10, 384);
        if (tid < 3 && wgi == 0) mbar_arrive(bars + 8 * (B_U + 2 * tid));
      } else {
        h_store(st0, warp * 64 + lane, H);
        ep = __shfl_sync(~0u, ep, 0) + 1;
        mbar_wait(bars + 8 * B_LN, 0);
        ln_rows(sb + CV_LN + warp * 16 * 1280, P.s->stats + 2 * p0 + warp * 16, 2 * (p1 - p0) - warp * 16, ep, lane);
        bar_arrive(10, 384);
        bar_sync(1 + wgi, 128);
        if (warp == 1) {
          if (elect()) { bulk_s2g(P.out + (size_t)p0 * 2 * D_, sb + CV_LN, (p1 - p0) * 2560); bulk_commit(); }
          __syncwarp();
        }
      }
    } else {
      {
        if (warp == 3) {
          const uint4 b = __ldg((const uint4*)(P.b1 + f * 256 + lane * 8));
          const uint32_t ba = xa + (lane >> 3) * 2048, l7 = lane & 7;
#pragma unroll
          for (int r = 6; r < 16; r++) sts128(ba + r * 128 + (l7 << 4), 0, 0, 0, 0);
          sts128(ba + 3 * 128 + ((l7 ^ 3) << 4), b.x, b.y, b.z, b.w);
          sts128(ba + 4 * 128 + ((l7 ^ 4) << 4), b.x, b.y, b.z, b.w);
          sts32(bars + 8 * B_NUM, ep + 1);
          if (lane == 0) map_prefetch(&tm_ur);
          fence_async_smem();
          __syncwarp();
          if (lane == 0) mbar_arrive(bars + 8 * B_BEXT);
        }
        mbar_wait(bars + 8 * (B_WF + J3_GATE), 0);
        const __nv_bfloat16* wp = P.w1 + (size_t)(mt * 40 + warp * 10) * F_ + f * 256 + lane * 8;
        uint4 w[10];
#pragma unroll
        for (int j = 0; j < 10; j++) w[j] = ldg128(wp + j * F_);
        float a[8] = {0.f, 0.f, 0.f, 0.f, 0.f, 0.f, 0.f, 0.f};
#pragma unroll
        for (int j = 0; j < 10; j++) {
          a[0] += bf_lo(w[j].x); a[1] += bf_hi(w[j].x); a[2] += bf_lo(w[j].y); a[3] += bf_hi(w[j].y);
          a[4] += bf_lo(w[j].z); a[5] += bf_hi(w[j].z); a[6] += bf_lo(w[j].w); a[7] += bf_hi(w[j].w);
        }
        ep = __shfl_sync(~0u, ep, 0) + 1;
        float* cp = (float*)(P.s->cs + (((ep & 1) * 4 + warp) * 6 + f) * 96 + lane);
        red4f(cp, a[0], a[1], a[2], 1.f); red4f(cp + 128, a[3], a[4], a[5], 1.f); red4f(cp + 256, a[6], a[7], 0.f, 1.f);
        kv_load(P, unit, lane, K);
        kv_load(P, unit + 384, lane, K1);
        h_load(P, ch0, warp * 64 + lane, H);
      }
      {
        const uint32_t s0 = xa + 8192 + warp * 2048, s1 = xa + 16384 + warp * 2048, lo = (lane & 15) * 32 + (lane < 16 ? 16 : 0);
        kv_finish(K, s0 + lo, 512, 1024, 1536);
        kv_finish(K1, s1 + lo, 512, 1024, 1536);
        h_store(st0, warp * 64 + lane, H);
        fence_async_smem();
        __syncwarp();
        if (elect()) {
          tma_st3(&tm_ur, S_ - 16 - (unit & 127) * 16, (unit >> 7) * 16, s0);
          tma_st3(&tm_ur, S_ - 16 - (unit & 127) * 16, (unit >> 7) * 16 + 48, s1);
          bulk_commit();
          bulk_wait<0>();
          flag_add_relaxed(P.s->cnt, C_KV + (unit >> 7)); flag_add_relaxed(P.s->cnt, C_KV + 3 + (unit >> 7));
        }
        bar_sync(1 + wgi, 128);
        if (warp == 2) zero_xch(xa, lane);
      }
      if (warp == 0 && elect()) {
        map_prefetch(&tm_out); map_prefetch(&tm_yt); map_prefetch(&tm_x64);
        conv_issue_u(P, ch0, st0 + ST_U, ubar, ep, ep * 128 - 1);
      }
      if (warp == 1 && mi < 4) {
#pragma unroll 1
        for (int i = lane; i < 576; i += 32) P.s->cs[((ep + 1) & 1) * 2304 + mi * 576 + i] = make_float4(0.f, 0.f, 0.f, 0.f);
      }
      if (warp == 2 && lane == 0) { flag_wait(P.s->cnt, C_INIT, ep * 36); mbar_arrive(bars + 8 * B_INIT); }
      bar_sync(6, 384);
    }
    if (is_conv && CSTAG) __nanosleep(wgi * CSTAG);
    conv_run(P, ch0, ch1, ch2, ch3, is_conv ? (wgi < 2 ? 3 : 2) : 0, sb + CV_UX + wgi * ST_H0, is_conv ? 4 : (f == 5 ? 3 : 2), xa, yb, st0,
             is_conv ? 2 : 1, ubar, 1 + wgi, ep, warp, lane);
    if (!is_conv && f < 5) {
      bar_sync(1 + wgi, 128);
      if (warp == 0 && elect()) {
        flag_wait(P.s->cnt, C_Y + f, ep * 128);
        fence_async();
        mbar_expect(bars + 8 * B_Y, 32768);
        tma_ld(sb + OFF_C, &tm_yt, mt * 128, f * 128, bars + 8 * B_Y);
        tma_ld(sb + OFF_C + 16384, &tm_yt, mt * 128 + 64, f * 128, bars + 8 * B_Y);
      }
    }
    if (blockIdx.x == NCTA - 1 && tid == 0) {
#pragma unroll 1
      for (int i = 0; i < 5; i++) flag_wait(P.s->cnt, C_Y + i, ep * 128);
      flag_add_relaxed(P.s->cnt, C_EPOCH);
    }
  } else {
    const int w = wgi, tid = warp * 32 + lane, g = lane >> 2, t4 = lane & 3;
    auto chunk_of = [&](int qi) { int q = f + 1 + qi; return f == 5 ? qi : q >= 5 ? q - 5 : q; };
    auto load_stage = [&](int v) {
      const uint32_t sl = v & 3, fb = bars + 8 * (B_WF + sl), dst = sb + OFF_W + sl * 32768 + rank * 16384;
      if (v >= 4) mbar_wait(bars + 8 * (B_WE + sl), ((v >> 2) - 1) & 1);
      if (elect()) {
        if (v < 10) {
          mbar_expect(fb, 49152);
          tma_ld3_mc(dst, &tm_w1, v * 64, f * 4 + rank * 2, fb);
          tma_ld(sb + OFF_X + sl * 16384, &tm_x, v * 64, mt * 128, fb);
        } else {
          mbar_expect(fb, 32768);
          tma_ld3_mc(dst, &tm_w2, f * 256 + (v & 1) * 128, chunk_of((v - 10) >> 1) * 2 + rank, fb);
        }
      }
      __syncwarp();
    };
    const uint32_t we_l = bars + 8 * B_WE, we_r = mapa(we_l, rank ^ 1);
    auto release = [&](uint32_t sl) { if (warp == 0 && elect()) { mbar_arrive(we_l + 8 * sl); mbar_arrive_cl(we_r + 8 * sl); } };
    cluster_wait();
    if (w == 1 && warp == 0) {
#pragma unroll 1
      for (int v = 1; v < 4; v++) { if (v == FIRST_GATE) mbar_wait(bars + 8 * B_WF, 0); load_stage(v); }
    }
    uint32_t hf[64];
    {
      float d[128];
      const uint32_t xlo = ((sb + OFF_X + w * 8192) & 0x3FFFF) >> 4;
      const uint32_t wlo = (((sb + OFF_W) & 0x3FFFF) >> 4) | (512u << 16);
      auto issue = [&](int v) {
        const uint32_t sl = v & 3;
        mbar_wait(bars + 8 * (B_WF + sl), (v >> 2) & 1);
        const uint32_t a = xlo + sl * 1024, b = wlo + sl * 2048;
        wg_fence();
        wg_ss256(d, a, b, v != 0);
        wg_ss256(d, a + 2, b + 128, 1);
        wg_ss256(d, a + 4, b + 256, 1);
        wg_ss256(d, a + 6, b + 384, 1);
        wg_commit();
      };
      auto retire = [&](int v) {
        wg_wait<1>();
        if (v > 0) {
          release((v - 1) & 3);
          if (w == 1 && warp == 0) load_stage(v + 3);
        }
      };
#pragma unroll 1
      for (int v = 0; v < EXTV; v++) {
        issue(v);
        if (v == W2PF && w == 0 && warp == 1 && (mc & 7) < 5 && elect()) {
          tma_prefetch3(&tm_w2, f * 256, (mc & 7) * 2 + rank); tma_prefetch3(&tm_w2, f * 256 + 128, (mc & 7) * 2 + rank);
        }
        retire(v);
      }
      issue(EXTV);
      mbar_wait(bars + 8 * B_BEXT, 0);
      const unsigned ep = lds32(bars + 8 * B_NUM);
      const float4* sp = P.s->stats + mt * 128 + w * 64 + warp * 16 + g;
      const float4* cq = P.s->cs + (((ep & 1) * 4 + 2 * (tid & 1)) * 6 + f) * 96 + w * 48 + (tid < 96 ? tid >> 1 : 0);
      float4 sa = ld_relaxed4(sp), sc = ld_relaxed4(sp + 8), v0 = ld_relaxed4(cq), v1 = ld_relaxed4(cq + 576);
      retire(EXTV);
      issue(EXTV + 1);
      uint32_t e0, e1;
      {
#pragma unroll 1
        for (int n = 0; n < 400000; n++) {
          if (__all_sync(~0u, v0.w + v1.w == 32.f && __float_as_uint(sa.z) == ep && __float_as_uint(sc.z) == ep && sa.w == sc.w)) break;
          sa = ld_relaxed4(sp); sc = ld_relaxed4(sp + 8); v0 = ld_relaxed4(cq); v1 = ld_relaxed4(cq + 576);
        }
          float4 u = make_float4(v0.x + v1.x, v0.y + v1.y, v0.z + v1.z, 0.f);
          u.x += __shfl_xor_sync(~0u, u.x, 1); u.y += __shfl_xor_sync(~0u, u.y, 1); u.z += __shfl_xor_sync(~0u, u.z, 1);
          if (tid < 96) {
            const int i = w * 48 + (tid >> 1), l = i & 31, p = i >> 5;
            const uint32_t h01 = pack2(-u.x, -u.y), h2 = pack2(-u.z, 0.f);
            uint32_t e01 = h01, e2 = h2;
            if (tid & 1) { e01 = pack2(-u.x - bf_lo(h01), -u.y - bf_hi(h01)); e2 = pack2(-u.z - bf_lo(h2), 0.f); }
            const uint32_t ba = sb + OFF_C + (l >> 3) * 2048 + p * 6;
#pragma unroll
            for (int q = 0; q < 2; q++) {
              const uint32_t r = (tid & 1) ? 1 + 4 * q : 2 * q, a = ba + r * 128 + (((l & 7) ^ r) << 4);
              asm volatile("st.shared.u16 [%0], %1;" :: "r"(a), "h"((uint16_t)e01) : "memory");
              asm volatile("st.shared.u16 [%0], %1;" :: "r"(a + 2), "h"((uint16_t)(e01 >> 16)) : "memory");
              if (p < 2) asm volatile("st.shared.u16 [%0], %1;" :: "r"(a + 4), "h"((uint16_t)e2) : "memory");
            }
          }
          if (t4 == 0) {
            asm volatile("st.shared.v2.f32 [%0], {%1,%2};" :: "r"(sb + OFF_STAT + (w * 64 + warp * 16 + g) * 8), "f"(sa.x), "f"(sa.y) : "memory");
            asm volatile("st.shared.v2.f32 [%0], {%1,%2};" :: "r"(sb + OFF_STAT + (w * 64 + warp * 16 + g + 8) * 8), "f"(sc.x), "f"(sc.y) : "memory");
          }
          fence_async_smem();
          const float da = rcp_fast(sa.y), dc = rcp_fast(sc.y);
          const float mha = bf_round(sa.x), mhc = bf_round(sc.x), dha = bf_round(da), dhc = bf_round(dc);
          const float x0 = t4 == 0 ? mha : t4 == 1 ? sa.x - mha : da - dha, x1 = t4 == 0 ? mha : t4 == 1 ? dha : sa.x - mha;
          const float y0 = t4 == 0 ? mhc : t4 == 1 ? sc.x - mhc : dc - dhc, y1 = t4 == 0 ? mhc : t4 == 1 ? dhc : sc.x - mhc;
          e0 = t4 == 3 ? 0u : pack2(x0, x1); e1 = t4 == 3 ? 0u : pack2(y0, y1);
      }
      retire(EXTV + 1);
#pragma unroll 1
      for (int v = EXTV + 2; v < 10; v++) { issue(v); retire(v); }
      bar_sync(5, 256);
      wg_fence();
      wg_rs256(d, e0, e1, 0u, 0u, (((sb + OFF_C) & 0x3FFFF) >> 4) | (128u << 16), 1);
      wg_commit();
      wg_wait<0>();
      bar_arrive(6, 384);
      release(1);
      if (w == 1 && warp == 0) load_stage(13);
      const float k0 = 0.7978845608028654f, k1 = 0.7978845608028654f * 0.044715f;
      const float ra = lds64f(sb + OFF_STAT + (w * 64 + warp * 16 + g) * 8).y, rc = lds64f(sb + OFF_STAT + (w * 64 + warp * 16 + g + 8) * 8).y;
      const float h0 = 0.5f * ra, c10 = k0 * ra, c30 = k1 * ra * ra * ra;
      const float h1 = 0.5f * rc, c11 = k0 * rc, c31 = k1 * rc * rc * rc;
#pragma unroll
      for (int i = 0; i < 64; i++) {
        const float hh = (i & 1) ? h1 : h0, c1 = (i & 1) ? c11 : c10, c3 = (i & 1) ? c31 : c30;
        const float a = d[2 * i], b = d[2 * i + 1];
        const float ta = tanh_fast(a * fmaf(a * a, c3, c1)), tb = tanh_fast(b * fmaf(b * b, c3, c1));
        const float pa = a * hh, pb = b * hh;
        hf[i] = pack2(fmaf(pa, ta, pa), fmaf(pb, tb, pb));
      }
    }
    {
      float d[64];
      const uint32_t wlo = (((sb + OFF_W) & 0x3FFFF) >> 4) | (1024u << 16);
      const uint32_t sta = sb + OFF_X + w * 32768 + (warp * 16 + (lane & 15)) * 128;
      const int l7 = lane & 7;
#pragma unroll 1
      for (int qi = 0; qi < 5; qi++) {
        const int q = chunk_of(qi);
        const uint32_t hb = ((qi + 1) & 1) * 2, ph = ((qi + 5) >> 1) & 1;
        if (w == 1) bar_sync(7 + 2 * (qi & 1), 256); else if (qi >= 1) bar_sync(8, 256); else if (f == 5) bar_sync(12, 256);
#pragma unroll
        for (int j = 0; j < 2; j++) {
          mbar_wait(bars + 8 * (B_WF + hb + j), ph);
          const uint32_t b = wlo + (hb + j) * 2048;
          wg_fence();
#pragma unroll
          for (int kk = 0; kk < 8; kk++) wg_rs128(d, &hf[32 * j + 4 * kk], b + 128 * kk, j + kk != 0);
          wg_commit();
          if (j == 0 && w == 0 && warp == 0 && qi >= 1 && qi < 4) load_stage(13 + 2 * qi);
        }
        if (w == 0) bar_arrive(7 + 2 * (qi & 1), 256); else if (qi < 4) bar_arrive(8, 256);
        wg_wait<1>();
        if (qi < 3) { release(hb); if (w == 1 && warp == 0) load_stage(14 + 2 * qi); }
        wg_wait<0>();
        if (qi < 3) release(hb + 1);
        if (qi == 0) { mbar_wait(we_l + 8, 0); mbar_wait(bars + 8 * B_INIT, 0); fence_async(); }
        const uint32_t st = sta + (qi & 1) * 16384;
        if (qi == 4 && f < 5) {
          const float2 s0 = lds64f(sb + OFF_STAT + (w * 64 + warp * 16 + g) * 8), s1 = lds64f(sb + OFF_STAT + (w * 64 + warp * 16 + g + 8) * 8);
          const uint32_t ma = pack2(s0.x, s0.x), ra = pack2(s0.y, s0.y), mb = pack2(s1.x, s1.x), rb = pack2(s1.y, s1.y);
          const uint32_t ya = sb + OFF_C + w * 16384 + (8 * (lane >> 4) + l7) * 128 + (((2 * warp + ((lane >> 3) & 1)) ^ l7) << 4);
          mbar_wait(bars + 8 * B_XT, 0);
#pragma unroll
          for (int cp = 0; cp < 8; cp++) {
            uint32_t xr[4];
            ldsm4(st + (cp >> 2) * 8192 + (((2 * (cp & 3) + (lane >> 4)) ^ l7) << 4), xr);
            const uint32_t b0 = ldg32(P.b2 + q * 128 + t4 * 2 + cp * 16), b1 = ldg32(P.b2 + q * 128 + t4 * 2 + cp * 16 + 8);
            hf[4 * cp] = hmul2(hsub2(xr[0], ma), ra); hf[4 * cp + 1] = hmul2(hsub2(xr[1], mb), rb);
            hf[4 * cp + 2] = hmul2(hsub2(xr[2], ma), ra); hf[4 * cp + 3] = hmul2(hsub2(xr[3], mb), rb);
            hf[32 + 4 * cp] = pack2(d[8 * cp] + bf_lo(b0), d[8 * cp + 1] + bf_hi(b0)); hf[33 + 4 * cp] = pack2(d[8 * cp + 2] + bf_lo(b0), d[8 * cp + 3] + bf_hi(b0));
            hf[34 + 4 * cp] = pack2(d[8 * cp + 4] + bf_lo(b1), d[8 * cp + 5] + bf_hi(b1)); hf[35 + 4 * cp] = pack2(d[8 * cp + 6] + bf_lo(b1), d[8 * cp + 7] + bf_hi(b1));
          }
          mbar_wait(bars + 8 * B_Y, 0);
#pragma unroll
          for (int cp = 0; cp < 8; cp++) {
            uint32_t yr[4];
            ldsm4t(ya + cp * 2048, yr);
            stsm4(st + (cp >> 2) * 8192 + (((2 * (cp & 3) + (lane >> 4)) ^ l7) << 4), hfma2(hf[4 * cp], yr[0], hf[32 + 4 * cp]), hfma2(hf[4 * cp + 1], yr[1], hf[33 + 4 * cp]),
                  hfma2(hf[4 * cp + 2], yr[2], hf[34 + 4 * cp]), hfma2(hf[4 * cp + 3], yr[3], hf[35 + 4 * cp]));
          }
        } else {
#pragma unroll
          for (int cp = 0; cp < 8; cp++) {
            const uint32_t a = st + (cp >> 2) * 8192 + (((2 * (cp & 3) + (lane >> 4)) ^ l7) << 4);
            stsm4(a, pack2(d[8 * cp], d[8 * cp + 1]), pack2(d[8 * cp + 2], d[8 * cp + 3]), pack2(d[8 * cp + 4], d[8 * cp + 5]), pack2(d[8 * cp + 6], d[8 * cp + 7]));
          }
        }
        fence_async_smem();
        if (warp == 0) bulk_wait_read<0>();
        bar_sync(1 + wgi, 128);
        if (warp == 0 && elect()) {
          const uint32_t src = sb + OFF_X + w * 32768 + (qi & 1) * 16384;
          tma_red(&tm_out, q * 128, mt * 128 + w * 64, src);
          tma_red(&tm_out, q * 128 + 64, mt * 128 + w * 64, src + 8192);
          bulk_commit();
          if (qi == 3 && f < 5) {
            const uint32_t dst = sb + OFF_X + w * 32768;
            mbar_expect(bars + 8 * B_XT, 16384);
            tma_ld(dst, &tm_x64, f * 128, mt * 128 + w * 64, bars + 8 * B_XT);
            tma_ld(dst + 8192, &tm_x64, f * 128 + 64, mt * 128 + w * 64, bars + 8 * B_XT);
          }
        }
      }
      if (warp == 0) bulk_wait_read<0>();
    }
  }
}

__device__ float g_fb_xn[S_ * D_], g_fb_kv[S_ * D_], g_fb_h[S_ * F_];
__device__ __forceinline__ float fbf(const __nv_bfloat16* p, size_t i) { return __bfloat162float(p[i]); }
__global__ void fb_pre(Params P) {
  const int t = blockIdx.x;
  __shared__ float red[2];
  if (threadIdx.x == 0) {
    float m = 0.f, v = 0.f;
    for (int i = 0; i < D_; i++) m += fbf(P.x, t * D_ + i);
    m /= D_;
    for (int i = 0; i < D_; i++) { const float d = fbf(P.x, t * D_ + i) - m; v += d * d; }
    red[0] = m; red[1] = rsqrtf(v / D_ + 1e-5f);
  }
  __syncthreads();
  for (int c = threadIdx.x; c < D_; c += blockDim.x) {
    g_fb_xn[t * D_ + c] = (fbf(P.x, t * D_ + c) - red[0]) * red[1];
    float a = 0.f;
    for (int j = 0; j < 4; j++) if (t - j >= 0) a += fbf(P.k, (t - j) * D_ + c) * fbf(P.shift, c * 4 + j);
    g_fb_kv[t * D_ + c] = bf_round(bf_round(a) * fbf(P.v, t * D_ + c));
  }
  __syncthreads();
  for (int n = threadIdx.x; n < F_; n += blockDim.x) {
    float a = fbf(P.b1, n);
    for (int k = 0; k < D_; k++) a += g_fb_xn[t * D_ + k] * fbf(P.w1, (size_t)k * F_ + n);
    g_fb_h[t * F_ + n] = 0.5f * a * (1.f + tanhf(0.7978845608f * (a + 0.044715f * a * a * a)));
  }
}
__global__ void fb_post(Params P, const __nv_bfloat16* w2) {
  const int t = blockIdx.x;
  for (int c = threadIdx.x; c < D_; c += blockDim.x) {
    float y = g_fb_kv[t * D_ + c] * fbf(P.dv, c), a = fbf(P.b2, c);
    for (int j = 0; j <= t; j++) y += g_fb_kv[(t - j) * D_ + c] * fbf(P.h, (size_t)c * S_ + j);
    for (int k = 0; k < F_; k++) a += g_fb_h[t * F_ + k] * fbf(w2, (size_t)k * D_ + c);
    P.out[t * D_ + c] = __float2bfloat16(fbf(P.x, t * D_ + c) + g_fb_xn[t * D_ + c] * y + a);
  }
}

typedef CUresult (*EncodeFn)(CUtensorMap*, CUtensorMapDataType, cuuint32_t, void*, const cuuint64_t*, const cuuint64_t*, const cuuint32_t*,
                             const cuuint32_t*, CUtensorMapInterleave, CUtensorMapSwizzle, CUtensorMapL2promotion, CUtensorMapFloatOOBfill);

CUtensorMap make_map(EncodeFn enc, const void* p, uint64_t d0, uint64_t d1, uint32_t b0, uint32_t b1) {
  CUtensorMap m;
  cuuint64_t gd[2] = {d0, d1}, gs[1] = {d0 * 2};
  cuuint32_t bx[2] = {b0, b1}, es[2] = {1, 1};
  enc(&m, CU_TENSOR_MAP_DATA_TYPE_BFLOAT16, 2, const_cast<void*>(p), gd, gs, bx, es, CU_TENSOR_MAP_INTERLEAVE_NONE,
      CU_TENSOR_MAP_SWIZZLE_128B, XPROMO, CU_TENSOR_MAP_FLOAT_OOB_FILL_NONE);
  return m;
}

CUtensorMap make_map3(EncodeFn enc, const void* p, uint64_t cols, uint64_t rows, uint32_t brows, uint32_t bgroups) {
  CUtensorMap m;
  cuuint64_t gd[3] = {64, rows, cols / 64}, gs[2] = {cols * 2, 128};
  cuuint32_t bx[3] = {64, brows, bgroups}, es[3] = {1, 1, 1};
  enc(&m, CU_TENSOR_MAP_DATA_TYPE_BFLOAT16, 3, const_cast<void*>(p), gd, gs, bx, es, CU_TENSOR_MAP_INTERLEAVE_NONE,
      CU_TENSOR_MAP_SWIZZLE_128B, CU_TENSOR_MAP_L2_PROMOTION_L2_256B, CU_TENSOR_MAP_FLOAT_OOB_FILL_NONE);
  return m;
}

CUtensorMap make_map8(EncodeFn enc, const void* p) {
  CUtensorMap m;
  cuuint64_t gd[3] = {D_, S_ / 8, 8}, gs[2] = {8 * D_ * 2, D_ * 2};
  cuuint32_t bx[3] = {8, 128, 8}, es[3] = {1, 1, 1};
  enc(&m, CU_TENSOR_MAP_DATA_TYPE_BFLOAT16, 3, const_cast<void*>(p), gd, gs, bx, es, CU_TENSOR_MAP_INTERLEAVE_NONE,
      CU_TENSOR_MAP_SWIZZLE_NONE, SLAB_PROMO, CU_TENSOR_MAP_FLOAT_OOB_FILL_NONE);
  return m;
}

CUtensorMap make_map_ur(EncodeFn enc, void* p) {
  CUtensorMap m;
  cuuint64_t gd[3] = {S_, D_ / 4, 4}, gs[2] = {4 * S_ * 2, S_ * 2};
  cuuint32_t bx[3] = {16, 16, 4}, es[3] = {1, 1, 1};
  enc(&m, CU_TENSOR_MAP_DATA_TYPE_BFLOAT16, 3, p, gd, gs, bx, es, CU_TENSOR_MAP_INTERLEAVE_NONE,
      CU_TENSOR_MAP_SWIZZLE_NONE, CU_TENSOR_MAP_L2_PROMOTION_NONE, CU_TENSOR_MAP_FLOAT_OOB_FILL_NONE);
  return m;
}

}

extern "C" void kernel_launch(void* const* d_in, const int* in_sizes, int n_in, void* d_out, int out_size) {
  (void)in_sizes; (void)n_in; (void)out_size;
  static EncodeFn enc = nullptr;
  static void* scr = nullptr;
  static bool resident = false;
  if (!enc) {
    void* fn = nullptr;
    cudaDriverEntryPointQueryResult q;
    cudaGetDriverEntryPoint("cuTensorMapEncodeTiled", &fn, cudaEnableDefault, &q);
    enc = (EncodeFn)fn;
    cudaGetSymbolAddress(&scr, g_scr);
    cudaFuncSetAttribute(fused_kernel, cudaFuncAttributeMaxDynamicSharedMemorySize, SMEM_BYTES);
    cudaLaunchConfig_t cfg = {};
    cfg.gridDim = dim3(NCTA); cfg.blockDim = dim3(NTHR); cfg.dynamicSmemBytes = SMEM_BYTES;
    cudaLaunchAttribute at;
    at.id = cudaLaunchAttributeClusterDimension; at.val.clusterDim.x = 2; at.val.clusterDim.y = 1; at.val.clusterDim.z = 1;
    cfg.attrs = &at; cfg.numAttrs = 1;
    int ncl = 0;
    resident = cudaOccupancyMaxActiveClusters(&ncl, fused_kernel, &cfg) == cudaSuccess && ncl >= NCTA / 2;
    (void)cudaGetLastError();
  }
  Params P;
  P.x = (const __nv_bfloat16*)d_in[0]; P.k = (const __nv_bfloat16*)d_in[1]; P.v = (const __nv_bfloat16*)d_in[2];
  P.shift = (const __nv_bfloat16*)d_in[3]; P.h = (const __nv_bfloat16*)d_in[4]; P.dv = (const __nv_bfloat16*)d_in[5];
  P.w1 = (const __nv_bfloat16*)d_in[7]; P.b1 = (const __nv_bfloat16*)d_in[8]; P.b2 = (const __nv_bfloat16*)d_in[10];
  P.out = (__nv_bfloat16*)d_out;
  P.s = (Scratch*)scr;
  if (!resident) {
    fb_pre<<<S_, 256>>>(P);
    fb_post<<<S_, 128>>>(P, (const __nv_bfloat16*)d_in[9]);
    return;
  }
  const CUtensorMap tm_x = make_map(enc, d_in[0], D_, S_, 64, 128), tm_x64 = make_map(enc, d_in[0], D_, S_, 64, 64);
  const CUtensorMap tm_w1 = make_map3(enc, d_in[7], F_, D_, 64, 2), tm_w2 = make_map3(enc, d_in[9], D_, F_, 128, 1);
  const CUtensorMap tm_out = make_map(enc, d_out, D_, S_, 64, 64), tm_yt = make_map(enc, P.s->yt, S_, D_, 64, 128);
  const CUtensorMap tm_k8 = make_map8(enc, d_in[1]), tm_v8 = make_map8(enc, d_in[2]);
  const CUtensorMap tm_ur = make_map_ur(enc, P.s->ur);
  fused_kernel<<<NCTA, NTHR, SMEM_BYTES>>>(P, tm_x, tm_x64, tm_w1, tm_w2, tm_out, tm_yt, tm_k8, tm_v8, tm_ur);
}
```
